```python
import torch

def _softmax(x, axis=-1):
    return torch.softmax(x, dim=axis)
def _gelu(x):
    return torch.nn.functional.gelu(x, approximate="tanh")
def _silu(x):
    return torch.nn.functional.silu(x)
def _sigmoid(x):
    return torch.sigmoid(x)
def _layernorm(x, axis=-1, eps=1e-5):
    m = x.mean(dim=axis, keepdim=True)
    v = x.var(dim=axis, keepdim=True, unbiased=False)
    return (x - m) / torch.sqrt(v + eps)
def _scatter_add(tgt, idx, src, axis=0):
    return tgt.clone().index_add_(axis, idx, src)
def _segment_sum(src, seg, n):
    out = torch.zeros((n,) + src.shape[1:], dtype=src.dtype)
    return out.index_add_(0, seg, src)
def _pad(x, pw):
    flat = tuple(v for pair in reversed(pw) for v in pair)
    return torch.nn.functional.pad(x, flat)

kernel_name = 'concat_heads__linear_kernel_hedgehog__compressed_kv_cla__prompt'

def setup_inputs():

    _w = (lambda a: (lambda t: t.to(torch.bfloat16) if t.is_floating_point() else t)(torch.as_tensor(a)))
    def _A_setup():
        B, S, D, H = 1, 2048, 512, 32
        Dh = D // H
        return {
            "x": _w((lambda *s: torch.randn(*s, dtype=torch.bfloat16) * 0.4)(B, S, D)),
            "wqkv": _w((lambda *s: torch.randn(*s, dtype=torch.bfloat16) * 0.4)(D, 3 * D)),
            "w_phi": _w((lambda *s: torch.randn(*s, dtype=torch.bfloat16) * 0.4)(H, Dh, Dh) * (Dh ** -0.5)),
            "wo": _w((lambda *s: torch.randn(*s, dtype=torch.bfloat16) * 0.05)(D, D)),
        }
    _A_in = _A_setup()

    def _B_setup():
        B, H, Sq, Sk, D, M = 1, 32, 2048, 2048, 128, 512
        Dc = 4 * D
        return {
            "x": _w((lambda *s: torch.randn(*s, dtype=torch.bfloat16) * 0.8)(B, Sq, M)),
            "c_kv": _w((lambda *s: torch.randn(*s, dtype=torch.bfloat16) * 0.4)(B, Sk, Dc)),
            "w_q": _w((lambda *s: torch.randn(*s, dtype=torch.bfloat16) * 6.4)(M, H, D) * (M ** -0.5)),
            "w_uk": _w((lambda *s: torch.randn(*s, dtype=torch.bfloat16) * 6.4)(Dc, H, D) * (Dc ** -0.5)),
            "w_uv": _w((lambda *s: torch.randn(*s, dtype=torch.bfloat16) * 0.4)(Dc, H, D) * (Dc ** -0.5)),
            "w_o": _w((lambda *s: torch.randn(*s, dtype=torch.bfloat16) * 0.4)(H, D, M) * ((H * D) ** -0.5)),
        }
    _B_in = _B_setup()

    return {
        "A_x": _A_in["x"],
        "A_wqkv": _A_in["wqkv"],
        "A_w_phi": _A_in["w_phi"],
        "A_wo": _A_in["wo"],
        "B_x": _B_in["x"],
        "B_c_kv": _B_in["c_kv"],
        "B_w_q": _B_in["w_q"],
        "B_w_uk": _B_in["w_uk"],
        "B_w_uv": _B_in["w_uv"],
        "B_w_o": _B_in["w_o"],
    }

def reference(A_x, A_wqkv, A_w_phi, A_wo, B_x, B_c_kv, B_w_q, B_w_uk, B_w_uv, B_w_o):
    def _A_ref(x, wqkv, w_phi, wo):
        B, S, D = x.shape
        H = 32; Dh = D // H
        qkv = (lambda x, *d: x.permute(*d))((x @ wqkv).reshape(B, S, 3, H, Dh), 2, 0, 3, 1, 4)
        q, k, v = qkv[0], qkv[1], qkv[2]
        pq = torch.einsum("bhsd,hdf->bhsf", q, w_phi)
        pk = torch.einsum("bhsd,hdf->bhsf", k, w_phi)
        phi_q = torch.concatenate([_softmax(pq, axis=-1), _softmax(-pq, axis=-1)], axis=-1)
        phi_k = torch.concatenate([_softmax(pk, axis=-1), _softmax(-pk, axis=-1)], axis=-1)
        kv = torch.einsum("bhsf,bhsd->bhfd", phi_k, v)
        z  = torch.einsum("bhsf->bhf", phi_k)
        num = torch.einsum("bhqf,bhfd->bhqd", phi_q, kv)
        den = torch.einsum("bhqf,bhf->bhq", phi_q, z)[..., None] + 1e-6
        o = num / den
        return (lambda x, *d: x.permute(*d))(o, 0, 2, 1, 3).reshape(B, S, D) @ wo

    def _B_ref(x, c_kv, w_q, w_uk, w_uv, w_o):
        B, Sq, M = x.shape[0], x.shape[1], x.shape[2]
        Sk = c_kv.shape[1]
        H, D = w_q.shape[1], w_q.shape[2]
        q = torch.einsum("bqm,mhd->bhqd", x, w_q)
        k = torch.einsum("bkc,chd->bhkd", c_kv, w_uk)
        v = torch.einsum("bkc,chd->bhkd", c_kv, w_uv)
        scores = torch.einsum("bhqd,bhkd->bhqk", q, k) * (D ** -0.5)
        off = Sk - Sq
        qi = torch.arange(Sq)[:, None]
        kj = torch.arange(Sk)[None, :]
        cmask = kj <= (qi + off)
        scores = torch.where(cmask[None, None], scores, -1e9)
        p = _softmax(scores, axis=-1)
        ctx = torch.einsum("bhqk,bhkd->bhqd", p, v)
        return torch.einsum("bhqd,hdm->bqm", ctx, w_o)

    a = _A_ref(A_x, A_wqkv, A_w_phi, A_wo)
    b = _B_ref(B_x, B_c_kv, B_w_q, B_w_uk, B_w_uv, B_w_o)
    return torch.concatenate([a, b], axis=-1)
```

```cpp
#include <cuda.h>
#include <cuda_runtime.h>
#include <cuda_bf16.h>
#include <stdint.h>

namespace {

constexpr int NSLOT = 7;
constexpr int SLOT_BYTES = 32768;
constexpr int NSIG = 20;
constexpr int OFF_FULL = NSLOT * SLOT_BYTES;
constexpr int OFF_EMPTY = OFF_FULL + 64;
constexpr int OFF_SIG = OFF_EMPTY + 64;
constexpr int SMEM_USED = OFF_SIG + 2 * NSIG * 8;
constexpr int SMEM_BYTES = SMEM_USED + 1024;

constexpr int FLAG_STRIDE = 8;
constexpr int F_HEAD = 0;
constexpr int F_CTX = F_HEAD + 32;
constexpr int F_AKV = F_CTX + 256;
constexpr int F_TAB = F_AKV + 8;
constexpr int F_XCH = F_TAB + 1;
constexpr int F_TOTAL = F_XCH + 1024;

struct Params {
    CUtensorMap xA, wqkv, woA, xB, ckv, wq, wuk, wuv, woB;
    const __nv_bfloat16* wphi;
    __nv_bfloat16* out;
};

__device__ uint4 g_q[32 * 16 * 2048];
__device__ uint4 g_k[32 * 16 * 2048];
__device__ uint4 g_v[32 * 16 * 2048];
__device__ float4 g_kvpart[32 * 32 * 136];
__device__ uint4 g_tab[32 * 4 * 32];
__device__ uint4 g_ospill[4 * 3 * 8 * 256];
__device__ float4 g_xch[128 * 3 * 8 * 256];
__device__ unsigned g_flags[F_TOTAL * FLAG_STRIDE];
__device__ unsigned g_epoch;

__device__ __forceinline__ uint32_t smem_u32(const void* p) { return (uint32_t)__cvta_generic_to_shared(p); }
__device__ __forceinline__ void mbar_init(uint32_t bar, uint32_t cnt) {
    asm volatile("mbarrier.init.shared::cta.b64 [%0], %1;" ::"r"(bar), "r"(cnt) : "memory");
}
__device__ __forceinline__ void mbar_expect_tx(uint32_t bar, uint32_t bytes) {
    asm volatile("mbarrier.arrive.expect_tx.shared::cta.b64 _, [%0], %1;" ::"r"(bar), "r"(bytes) : "memory");
}
__device__ __forceinline__ void mbar_arrive(uint32_t bar) {
    asm volatile("mbarrier.arrive.shared::cta.b64 _, [%0];" ::"r"(bar) : "memory");
}
__device__ __forceinline__ void mbar_arrive_cluster(uint32_t bar) {
    asm volatile("mbarrier.arrive.shared::cluster.b64 _, [%0];" ::"r"(bar) : "memory");
}
__device__ __forceinline__ void mbar_wait(uint32_t bar, uint32_t parity) {
    asm volatile(
        "{\n .reg .pred p;\n .reg .u32 c;\n mov.u32 c, 0;\n"
        "W_LOOP:\n mbarrier.try_wait.parity.shared::cta.b64 p, [%0], %1;\n @p bra W_DONE;\n"
        " add.u32 c, c, 1;\n setp.lt.u32 p, c, 2000000;\n @p bra W_LOOP;\n trap;\n W_DONE:\n }"
        ::"r"(bar), "r"(parity) : "memory");
}
__device__ __forceinline__ void flag_wait(const unsigned* p, unsigned target) {
    asm volatile(
        "{\n .reg .pred p;\n .reg .u32 c, v;\n .reg .s32 d;\n mov.u32 c, 0;\n"
        "F_LOOP:\n ld.acquire.gpu.global.u32 v, [%0];\n sub.s32 d, v, %1;\n setp.ge.s32 p, d, 0;\n @p bra F_DONE;\n"
        " nanosleep.u32 40;\n add.u32 c, c, 1;\n setp.lt.u32 p, c, 4000000;\n @p bra F_LOOP;\n trap;\n F_DONE:\n }"
        ::"l"(p), "r"(target) : "memory");
}
__device__ __forceinline__ void flag_add(unsigned* p) {
    asm volatile("red.relaxed.gpu.global.add.u32 [%0], 1;" ::"l"(p) : "memory");
}
__device__ __forceinline__ void fence_gpu() { asm volatile("fence.acq_rel.gpu;" ::: "memory"); }
__device__ __forceinline__ void fence_proxy_async() { asm volatile("fence.proxy.async;" ::: "memory"); }

__device__ __forceinline__ void bulk_load(uint32_t dst, const void* src, uint32_t bytes, uint32_t bar) {
    asm volatile("cp.async.bulk.shared::cluster.global.mbarrier::complete_tx::bytes [%0], [%1], %2, [%3];"
                 ::"r"(dst), "l"(src), "r"(bytes), "r"(bar) : "memory");
}
__device__ __forceinline__ void bulk_load_mc(uint32_t dst, const void* src, uint32_t bytes, uint32_t bar) {
    asm volatile("cp.async.bulk.shared::cluster.global.mbarrier::complete_tx::bytes.multicast::cluster [%0], [%1], %2, [%3], %4;"
                 ::"r"(dst), "l"(src), "r"(bytes), "r"(bar), "h"((uint16_t)3) : "memory");
}
__device__ __forceinline__ void tma_load(uint32_t dst, const CUtensorMap* m, int c0, int c1, uint32_t bar) {
    asm volatile("cp.async.bulk.tensor.2d.shared::cluster.global.mbarrier::complete_tx::bytes [%0], [%1, {%3, %4}], [%2];"
                 ::"r"(dst), "l"(m), "r"(bar), "r"(c0), "r"(c1) : "memory");
}
__device__ __forceinline__ void tma_load_mc(uint32_t dst, const CUtensorMap* m, int c0, int c1, uint32_t bar) {
    asm volatile("cp.async.bulk.tensor.2d.shared::cluster.global.mbarrier::complete_tx::bytes.multicast::cluster [%0], [%1, {%3, %4}], [%2], %5;"
                 ::"r"(dst), "l"(m), "r"(bar), "r"(c0), "r"(c1), "h"((uint16_t)3) : "memory");
}
__device__ __forceinline__ uint64_t make_desc(uint32_t addr, uint32_t lbo, uint32_t sbo) {
    return (uint64_t)((addr & 0x3FFFF) >> 4) | ((uint64_t)(lbo >> 4) << 16) | ((uint64_t)(sbo >> 4) << 32) | (1ull << 62);
}
__device__ __forceinline__ void wg_fence() { asm volatile("wgmma.fence.sync.aligned;" ::: "memory"); }
__device__ __forceinline__ void wg_commit() { asm volatile("wgmma.commit_group.sync.aligned;" ::: "memory"); }
template <int N> __device__ __forceinline__ void wg_wait() { asm volatile("wgmma.wait_group.sync.aligned %0;" ::"n"(N) : "memory"); }
template <int N> __device__ __forceinline__ void pin(float* a) {
#pragma unroll
    for (int i = 0; i < N; i++) asm volatile("" : "+f"(a[i])::"memory");
}
template <int N> __device__ __forceinline__ void pin(uint32_t* a) {
#pragma unroll
    for (int i = 0; i < N; i++) asm volatile("" : "+r"(a[i])::"memory");
}
__device__ __forceinline__ void bar_sync(int id, int n) { asm volatile("bar.sync %0, %1;" ::"r"(id), "r"(n) : "memory"); }
__device__ __forceinline__ void bar_arrive(int id, int n) { asm volatile("bar.arrive %0, %1;" ::"r"(id), "r"(n) : "memory"); }

#define R8(a, o) "+f"(a[o + 0]), "+f"(a[o + 1]), "+f"(a[o + 2]), "+f"(a[o + 3]), "+f"(a[o + 4]), "+f"(a[o + 5]), "+f"(a[o + 6]), "+f"(a[o + 7])
#define R32(a, o) R8(a, o), R8(a, o + 8), R8(a, o + 16), R8(a, o + 24)
#define R64(a, o) R32(a, o), R32(a, o + 32)
#define L32 "%0,%1,%2,%3,%4,%5,%6,%7,%8,%9,%10,%11,%12,%13,%14,%15,%16,%17,%18,%19,%20,%21,%22,%23,%24,%25,%26,%27,%28,%29,%30,%31"
#define L64 L32 ",%32,%33,%34,%35,%36,%37,%38,%39,%40,%41,%42,%43,%44,%45,%46,%47,%48,%49,%50,%51,%52,%53,%54,%55,%56,%57,%58,%59,%60,%61,%62,%63"
#define L128 L64 ",%64,%65,%66,%67,%68,%69,%70,%71,%72,%73,%74,%75,%76,%77,%78,%79,%80,%81,%82,%83,%84,%85,%86,%87,%88,%89,%90,%91,%92,%93,%94,%95" \
    ",%96,%97,%98,%99,%100,%101,%102,%103,%104,%105,%106,%107,%108,%109,%110,%111,%112,%113,%114,%115,%116,%117,%118,%119,%120,%121,%122,%123,%124,%125,%126,%127"

template <int TB>
__device__ __forceinline__ void wgmma_rs_n128(float* d, const uint32_t* a, uint64_t db, int acc) {
    asm volatile("{ .reg .pred p; setp.ne.b32 p, %69, 0;\n"
                 "wgmma.mma_async.sync.aligned.m64n128k16.f32.bf16.bf16 {" L64 "}, {%64,%65,%66,%67}, %68, p, 1, 1, %70; }"
                 : R64(d, 0) : "r"(a[0]), "r"(a[1]), "r"(a[2]), "r"(a[3]), "l"(db), "r"(acc), "n"(TB));
}
__device__ __forceinline__ void wgmma_rs_n64(float* d, const uint32_t* a, uint64_t db, int acc) {
    asm volatile("{ .reg .pred p; setp.ne.b32 p, %37, 0;\n"
                 "wgmma.mma_async.sync.aligned.m64n64k16.f32.bf16.bf16 {" L32 "}, {%32,%33,%34,%35}, %36, p, 1, 1, 0; }"
                 : R32(d, 0) : "r"(a[0]), "r"(a[1]), "r"(a[2]), "r"(a[3]), "l"(db), "r"(acc));
}
__device__ __forceinline__ void wgmma_ss_n256(float* d, uint64_t da, uint64_t db, int acc) {
    asm volatile("{ .reg .pred p; setp.ne.b32 p, %130, 0;\n"
                 "wgmma.mma_async.sync.aligned.m64n256k16.f32.bf16.bf16 {" L128 "}, %128, %129, p, 1, 1, 0, 1; }"
                 : R64(d, 0), R64(d, 64) : "l"(da), "l"(db), "r"(acc));
}
__device__ __forceinline__ void mma16816(float* c, const uint32_t* a, uint32_t b0, uint32_t b1) {
    asm volatile("mma.sync.aligned.m16n8k16.row.col.f32.bf16.bf16.f32 {%0,%1,%2,%3}, {%4,%5,%6,%7}, {%8,%9}, {%0,%1,%2,%3};"
                 : "+f"(c[0]), "+f"(c[1]), "+f"(c[2]), "+f"(c[3])
                 : "r"(a[0]), "r"(a[1]), "r"(a[2]), "r"(a[3]), "r"(b0), "r"(b1));
}
__device__ __forceinline__ void ldsm4(uint32_t* r, uint32_t addr) {
    asm volatile("ldmatrix.sync.aligned.m8n8.x4.shared.b16 {%0,%1,%2,%3}, [%4];"
                 : "=r"(r[0]), "=r"(r[1]), "=r"(r[2]), "=r"(r[3]) : "r"(addr) : "memory");
}
__device__ __forceinline__ void ldsm4t(uint32_t* r, uint32_t addr) {
    asm volatile("ldmatrix.sync.aligned.m8n8.x4.trans.shared.b16 {%0,%1,%2,%3}, [%4];"
                 : "=r"(r[0]), "=r"(r[1]), "=r"(r[2]), "=r"(r[3]) : "r"(addr) : "memory");
}
__device__ __forceinline__ void stsm4(uint32_t addr, uint32_t a, uint32_t b, uint32_t c, uint32_t d) {
    asm volatile("stmatrix.sync.aligned.m8n8.x4.shared.b16 [%0], {%1,%2,%3,%4};" ::"r"(addr), "r"(a), "r"(b), "r"(c), "r"(d) : "memory");
}
__device__ __forceinline__ uint32_t movm(uint32_t a) {
    uint32_t d;
    asm volatile("movmatrix.sync.aligned.m8n8.trans.b16 %0, %1;" : "=r"(d) : "r"(a));
    return d;
}
__device__ __forceinline__ uint32_t pack2(float lo, float hi) {
    uint32_t d;
    asm("cvt.rn.bf16x2.f32 %0, %1, %2;" : "=r"(d) : "f"(hi), "f"(lo));
    return d;
}
__device__ __forceinline__ float ex2(float x) {
    float y;
    asm("ex2.approx.ftz.f32 %0, %1;" : "=f"(y) : "f"(x));
    return y;
}
__device__ __forceinline__ float quad_max(float v) {
    v = fmaxf(v, __shfl_xor_sync(~0u, v, 1));
    return fmaxf(v, __shfl_xor_sync(~0u, v, 2));
}
__device__ __forceinline__ float quad_min(float v) {
    v = fminf(v, __shfl_xor_sync(~0u, v, 1));
    return fminf(v, __shfl_xor_sync(~0u, v, 2));
}
__device__ __forceinline__ float quad_sum(float v) {
    v += __shfl_xor_sync(~0u, v, 1);
    return v + __shfl_xor_sync(~0u, v, 2);
}
__device__ __forceinline__ uint4 quad_transpose(uint32_t r0, uint32_t r1, uint32_t r2, uint32_t r3, int q) {
    const bool b0 = q & 1, b1 = q & 2;
    uint32_t s0 = __shfl_xor_sync(~0u, b0 ? r0 : r1, 1), s1 = __shfl_xor_sync(~0u, b0 ? r2 : r3, 1);
    uint32_t t0 = b0 ? s0 : r0, t1 = b0 ? r1 : s0, t2 = b0 ? s1 : r2, t3 = b0 ? r3 : s1;
    s0 = __shfl_xor_sync(~0u, b1 ? t0 : t2, 2);
    s1 = __shfl_xor_sync(~0u, b1 ? t1 : t3, 2);
    return make_uint4(b1 ? s0 : t0, b1 ? s1 : t1, b1 ? t2 : s0, b1 ? t3 : s1);
}

struct Ring {
    uint32_t slot, phase;
    __device__ __forceinline__ void advance() {
        if (++slot == NSLOT) { slot = 0; phase ^= 1; }
    }
};

struct Producer {
    uint32_t base, rank;
    Ring r;
    __device__ __forceinline__ uint32_t acquire(uint32_t bytes, uint32_t& bar) {
        mbar_wait(base + OFF_EMPTY + 8 * r.slot, r.phase ^ 1);
        bar = base + OFF_FULL + 8 * r.slot;
        uint32_t dst = base + r.slot * SLOT_BYTES;
        if (bytes) mbar_expect_tx(bar, bytes); else mbar_arrive(bar);
        r.advance();
        return dst;
    }
    __device__ __forceinline__ void tokens(const CUtensorMap* m, int row0) {
#pragma unroll 1
        for (int s = 0; s < 4; s++) {
            uint32_t bar, dst = acquire(SLOT_BYTES, bar);
            tma_load(dst, m, s * 128, row0, bar);
            tma_load(dst + 16384, m, s * 128 + 64, row0, bar);
        }
    }
    __device__ __forceinline__ void wtile(const CUtensorMap* m, int col0, int col1) {
        const int col = rank ? col1 : col0;
#pragma unroll 1
        for (int s = 0; s < 4; s++) {
            uint32_t bar, dst = acquire(SLOT_BYTES, bar);
            tma_load_mc(dst + rank * 16384, m, col, s * 128, bar);
        }
    }
    __device__ __forceinline__ void shared_tile(const uint4* src) {
        uint32_t bar, dst = acquire(SLOT_BYTES, bar);
        bulk_load_mc(dst + rank * 16384, src + rank * 1024, 16384, bar);
    }
};

struct Consumer {
    uint32_t base, empty_remote;
    int wg, warp, lane;
    Ring r;
    __device__ __forceinline__ uint32_t take(uint32_t& slot) {
        slot = r.slot;
        mbar_wait(base + OFF_FULL + 8 * slot, r.phase);
        r.advance();
        return base + slot * SLOT_BYTES;
    }
    __device__ __forceinline__ void release(uint32_t slot) {
        if (lane < 2) mbar_arrive_cluster(empty_remote + 8 * slot);
    }
    __device__ __forceinline__ void turn_wait() { bar_sync(1 + wg, 256); }
    __device__ __forceinline__ void turn_pass() { bar_arrive(2 - wg, 256); }
    __device__ __forceinline__ void signal(int ev) {
        __syncwarp();
        if (lane == 0) mbar_arrive(base + OFF_SIG + (wg * NSIG + ev) * 8);
    }
    __device__ __forceinline__ void load_tokens(uint32_t* a) {
        const uint32_t row = wg * 64 + warp * 16 + (lane & 15);
#pragma unroll
        for (int s = 0; s < 4; s++) {
            uint32_t slot, sb = take(slot);
#pragma unroll
            for (int k = 0; k < 8; k++)
                ldsm4(a + (s * 8 + k) * 4, sb + (k >> 2) * 16384 + row * 128 + ((((k & 3) * 2 + (lane >> 4)) ^ (lane & 7)) << 4));
            pin<32>(a + s * 32);
            __syncwarp();
            release(slot);
        }
    }
    __device__ __forceinline__ void proj_tile(float* acc, uint32_t* a) {
        uint32_t slot, prev = 0;
        uint32_t sb = take(slot);
        turn_wait();
#pragma unroll
        for (int s = 0; s < 4; s++) {
            if (s > 0) sb = take(slot);
            wg_fence();
#pragma unroll
            for (int k = 0; k < 8; k++)
                wgmma_rs_n128<1>(acc, a + (s * 8 + k) * 4, make_desc(sb + k * 2048, 16384, 1024), (s | k) != 0);
            wg_commit();
            if (s == 3) turn_pass();
            if (s > 0) { wg_wait<1>(); release(prev); }
            prev = slot;
        }
        wg_wait<0>();
        pin<64>(acc);
        pin<128>(a);
        release(prev);
    }
};

__device__ __forceinline__ void store_tile(uint4* tile, int row, int lane, const float* acc, float s0, float s1) {
    const int g = lane >> 2, q = lane & 3;
#pragma unroll
    for (int a = 0; a < 4; a++) {
        const float* c = acc + a * 16;
        uint4* p = tile + (a >> 1) * 1024 + (row + g) * 8 + ((((a & 1) << 2) | q) ^ g);
        p[0] = make_uint4(pack2(c[0] * s0, c[1] * s0), pack2(c[4] * s0, c[5] * s0), pack2(c[8] * s0, c[9] * s0), pack2(c[12] * s0, c[13] * s0));
        p[64] = make_uint4(pack2(c[2] * s1, c[3] * s1), pack2(c[6] * s1, c[7] * s1), pack2(c[10] * s1, c[11] * s1), pack2(c[14] * s1, c[15] * s1));
    }
}

constexpr float LOG2E = 1.4426950408889634f;

__device__ __forceinline__ void feature_map(const float* p0, const float* p1, uint32_t* phi) {
#pragma unroll
    for (int th = 0; th < 2; th++) {
        const float a = p0[2 * th], b = p0[2 * th + 1], c = p1[2 * th], d = p1[2 * th + 1];
        const float mx = quad_max(fmaxf(fmaxf(a, b), fmaxf(c, d))) * LOG2E;
        const float mn = quad_min(fminf(fminf(a, b), fminf(c, d))) * LOG2E;
        const float ea = ex2(fmaf(a, LOG2E, -mx)), eb = ex2(fmaf(b, LOG2E, -mx));
        const float ec = ex2(fmaf(c, LOG2E, -mx)), ed = ex2(fmaf(d, LOG2E, -mx));
        const float na = ex2(fmaf(a, -LOG2E, mn)), nb = ex2(fmaf(b, -LOG2E, mn));
        const float nc = ex2(fmaf(c, -LOG2E, mn)), nd = ex2(fmaf(d, -LOG2E, mn));
        const float ip = __fdividef(1.f, quad_sum((ea + eb) + (ec + ed)));
        const float in = __fdividef(1.f, quad_sum((na + nb) + (nc + nd)));
        phi[0 + th] = pack2(ea * ip, eb * ip);
        phi[2 + th] = pack2(ec * ip, ed * ip);
        phi[4 + th] = pack2(na * in, nb * in);
        phi[6 + th] = pack2(nc * in, nd * in);
    }
}

__device__ __forceinline__ uint4 wphi_frags(const __nv_bfloat16* wphi, int head, int lane) {
    const uint32_t* w = reinterpret_cast<const uint32_t*>(wphi) + head * 128 + (lane >> 2) * 8 + (lane & 3);
    return make_uint4(movm(__ldg(w)), movm(__ldg(w + 64)), movm(__ldg(w + 4)), movm(__ldg(w + 68)));
}

#define PROF(i) do {} while (0)

constexpr float SM_SCALE = 0.08838834764831845f * LOG2E;

template <int N>
__device__ __forceinline__ void row_max(const float* s, float& m0, float& m1) {
#pragma unroll
    for (int j = 0; j < N / 4; j++) {
        m0 = fmaxf(m0, fmaxf(s[4 * j], s[4 * j + 1]));
        m1 = fmaxf(m1, fmaxf(s[4 * j + 2], s[4 * j + 3]));
    }
}
template <int N>
__device__ __forceinline__ void row_exp(float* s, float mc0, float mc1, float& l0, float& l1) {
#pragma unroll
    for (int j = 0; j < N / 4; j++) {
        s[4 * j] = ex2(fmaf(s[4 * j], SM_SCALE, -mc0));
        s[4 * j + 1] = ex2(fmaf(s[4 * j + 1], SM_SCALE, -mc0));
        s[4 * j + 2] = ex2(fmaf(s[4 * j + 2], SM_SCALE, -mc1));
        s[4 * j + 3] = ex2(fmaf(s[4 * j + 3], SM_SCALE, -mc1));
        l0 += s[4 * j] + s[4 * j + 1];
        l1 += s[4 * j + 2] + s[4 * j + 3];
    }
}
__device__ __forceinline__ void pack_p(uint32_t* p, const float* s) {
#pragma unroll
    for (int i = 0; i < 32; i++) p[i] = pack2(s[2 * i], s[2 * i + 1]);
}
__device__ __forceinline__ void issue_pv(float* o, const uint32_t* p, uint32_t vb, uint32_t lo, uint32_t hi, bool do_hi, int acc) {
#pragma unroll
    for (int k = 0; k < 4; k++) wgmma_rs_n128<1>(o, p + 4 * k, make_desc(vb + lo + k * 2048, 16384, 1024), k ? 1 : acc);
    if (do_hi) {
#pragma unroll
        for (int k = 0; k < 4; k++) wgmma_rs_n128<1>(o, p + 16 + 4 * k, make_desc(vb + hi + k * 2048, 16384, 1024), 1);
    }
}

__device__ __forceinline__ int item_block(int it, int tp) { return (it & 1) ? 7 - tp : tp; }
__device__ __forceinline__ int oproj_head(int ks, int n) { return 8 * ks + (n & 1) * 4 + (n >> 1); }

__global__ void __cluster_dims__(2, 1, 1) __launch_bounds__(384, 1)
fused_kernel(const __grid_constant__ Params prm) {
    extern __shared__ uint8_t smem_raw[];
    const uint32_t base = (smem_u32(smem_raw) + 1023) & ~1023u;
    const int tid = threadIdx.x;
    const int wgi = __shfl_sync(~0u, tid >> 7, 0);
    const int warp = __shfl_sync(~0u, (tid >> 5) & 3, 0);
    const int lane = tid & 31;
    const uint32_t rank = blockIdx.x & 1;
    const int cl = blockIdx.x >> 1;
    const bool extra = cl >= 64;
    const int tp = cl & 7, cg = cl >> 3;

    if (tid == 0) {
        for (int i = 0; i < NSLOT; i++) {
            mbar_init(base + OFF_FULL + 8 * i, 1);
            mbar_init(base + OFF_EMPTY + 8 * i, 16);
        }
        for (int i = 0; i < 2 * NSIG; i++) mbar_init(base + OFF_SIG + 8 * i, 4);
        asm volatile("fence.mbarrier_init.release.cluster;" ::: "memory");
    }
    __syncthreads();
    asm volatile("barrier.cluster.arrive.aligned;\n barrier.cluster.wait.aligned;" ::: "memory");

    if (wgi == 2) {
        asm volatile("setmaxnreg.dec.sync.aligned.u32 40;");
        if (warp == 0) {
            if (lane == 0) {
                Producer p{base, rank, {0, 0}};
                if (!extra) {
                    const int row0 = tp * 256 + rank * 128;
                    p.tokens(&prm.xA, row0);
                    p.wtile(&prm.wqkv, 512 + 64 * cg, 1024 + 64 * cg);
                    const unsigned ep = *(volatile unsigned*)&g_epoch + 1;
                    { uint32_t bar; p.acquire(0, bar); }
                    p.tokens(&prm.xB, row0);
#pragma unroll 1
                    for (int i = 0; i < 4; i++) p.wtile(&prm.wq, (4 * cg + i) * 128, (4 * cg + i) * 128 + 64);
                    p.tokens(&prm.ckv, row0);
#pragma unroll 1
                    for (int i = 0; i < 8; i++) {
                        const int col = (4 * cg + (i >> 1)) * 128;
                        p.wtile((i & 1) ? &prm.wuv : &prm.wuk, col, col + 64);
                    }
                    const uint4* vprev = nullptr;
#pragma unroll 1
                    for (int it = 0; it < 4; it++) {
                        const int h = 4 * cg + it, sb = item_block(it, tp);
                        flag_wait(&g_flags[(F_HEAD + h) * FLAG_STRIDE], ep * 96);
                        fence_proxy_async();
                        uint32_t bar, dst = p.acquire(SLOT_BYTES, bar);
#pragma unroll
                        for (int w = 0; w < 2; w++) {
                            const int rb = 4 * sb + (w == 0 ? 3 - rank : rank);
                            const uint4* src = g_q + (h * 16 + (rb >> 1)) * 2048 + (rb & 1) * 512;
                            bulk_load(dst + w * 16384, src, 8192, bar);
                            bulk_load(dst + w * 16384 + 8192, src + 1024, 8192, bar);
                        }
                        const uint4* kh = g_k + h * 16 * 2048;
                        const uint4* vh = g_v + h * 16 * 2048;
                        p.shared_tile(kh + (2 * sb + 1) * 2048);
                        if (vprev) p.shared_tile(vprev);
#pragma unroll 1
                        for (int t = 2 * sb; t >= 0; t--) {
                            p.shared_tile(kh + t * 2048);
                            p.shared_tile(vh + (t + 1) * 2048);
                        }
                        vprev = vh;
                    }
                    p.shared_tile(vprev);
#pragma unroll 1
                    for (int n = 0; n < 8; n++) {
                        const int h = oproj_head(cg >> 1, n);
                        flag_wait(&g_flags[(F_CTX + h * 8 + tp) * FLAG_STRIDE], ep * 4);
                        fence_proxy_async();
                        uint32_t bar, dst = p.acquire(SLOT_BYTES, bar);
                        bulk_load(dst, g_q + (h * 16 + tp * 2 + rank) * 2048, SLOT_BYTES, bar);
#pragma unroll
                        for (int kh = 0; kh < 2; kh++) {
                            dst = p.acquire(SLOT_BYTES, bar);
                            const int col = (cg & 1) * 256 + rank * 128, row = h * 128 + kh * 64;
                            tma_load_mc(dst + rank * 16384, &prm.woB, col, row, bar);
                            tma_load_mc(dst + rank * 16384 + 8192, &prm.woB, col + 64, row, bar);
                        }
                    }
                } else {
#pragma unroll 1
                    for (int b = 0; b < 4; b++) {
                        p.tokens(&prm.xA, ((cl - 64) * 4 + b) * 256 + rank * 128);
#pragma unroll 1
                        for (int i = 0; i < 8; i++)
                            p.wtile(i < 4 ? &prm.wqkv : &prm.woA, (i & 3) * 128, (i & 3) * 128 + 64);
                    }
                }
            }
        } else if (warp < 3) {
            if (lane == 0 && !extra) {
                const int w = warp - 1;
#pragma unroll 1
                for (int ev = 0; ev < 17; ev++) {
                    mbar_wait(base + OFF_SIG + (w * NSIG + ev) * 8, 0);
                    int f;
                    if (ev == 0) f = F_AKV + cg;
                    else if (ev < 5) f = F_HEAD + 4 * cg + ev - 1;
                    else if (ev < 13) f = F_HEAD + 4 * cg + ((ev - 5) >> 1);
                    else f = F_CTX + (4 * cg + ev - 13) * 8 + item_block(ev - 13, tp);
                    fence_gpu();
                    flag_add(&g_flags[f * FLAG_STRIDE]);
                }
            }
        } else {
            const unsigned ep = *(volatile unsigned*)&g_epoch + 1;
            if (!extra) {
                const int u = tp * 2 + rank, head = 4 * cg + (u >> 2), part = u & 3;
                const uint4 wf = wphi_frags(prm.wphi, head, lane);
                if (part == 0) g_tab[(head * 4 + 0) * 32 + lane] = wf;
                flag_wait(&g_flags[(F_AKV + cg) * FLAG_STRIDE], ep * 32);
                const float4* src = g_kvpart + head * 32 * 136;
                float4 s = make_float4(0.f, 0.f, 0.f, 0.f);
                float2 z = make_float2(0.f, 0.f);
#pragma unroll 4
                for (int i = 0; i < 32; i++) {
                    const float4 v = __ldcg(src + i * 136 + part * 32 + lane);
                    const float2 y = __ldcg(reinterpret_cast<const float2*>(src + i * 136 + 128) + part * 4 + (lane & 3));
                    s.x += v.x; s.y += v.y; s.z += v.z; s.w += v.w;
                    z.x += y.x; z.y += y.y;
                }
                uint32_t* t = reinterpret_cast<uint32_t*>(g_tab + head * 128);
                t[((1 + (part >> 1)) * 32 + lane) * 4 + (part & 1)] = pack2(s.x, s.y);
                t[((1 + (part >> 1)) * 32 + lane) * 4 + 2 + (part & 1)] = pack2(s.z, s.w);
                t[(3 * 32 + lane) * 4 + part] = pack2(z.x, z.y);
                __syncwarp();
            }
            if (lane == 0) {
                fence_gpu();
                flag_add(&g_flags[F_TAB * FLAG_STRIDE]);
            }
        }
    } else {
        asm volatile("setmaxnreg.inc.sync.aligned.u32 232;");
        Consumer c;
        c.base = base; c.wg = wgi; c.warp = warp; c.lane = lane; c.r = {0, 0};
        asm("mapa.shared::cluster.u32 %0, %1, %2;" : "=r"(c.empty_remote) : "r"(base + OFF_EMPTY), "r"(lane & 1));
        const int g = lane >> 2, q = lane & 3;
        const unsigned ep = *(volatile unsigned*)&g_epoch + 1;
        if (wgi == 1) bar_arrive(1, 256);
        PROF(0);

        if (!extra) {
            const int tb = tp * 2 + rank;
            {
                uint32_t a[128];
                float acc[64];
                c.load_tokens(a);
                c.proj_tile(acc, a);
                PROF(1);
                {
                    uint32_t slot;
                    const uint32_t sc = c.take(slot) + wgi * 16384;
                    const int head = 4 * cg + warp;
                    const uint4 wf = wphi_frags(prm.wphi, head, lane);
                    const uint32_t srow = warp * 16 + (lane & 15);
#pragma unroll
                    for (int jj = 0; jj < 8; jj++) {
                        const float* x = acc + jj * 8;
                        stsm4(sc + (jj >> 2) * 8192 + srow * 128 + ((((jj & 3) * 2 + (lane >> 4)) ^ (lane & 7)) << 4),
                              pack2(x[0], x[1]), pack2(x[2], x[3]), pack2(x[4], x[5]), pack2(x[6], x[7]));
                    }
                    bar_sync(3 + wgi, 128);
                    float kv[16], zz[16];
#pragma unroll
                    for (int i = 0; i < 16; i++) { kv[i] = 0.f; zz[i] = 0.f; }
                    const uint32_t ones[4] = {0x3F803F80u, 0x3F803F80u, 0x3F803F80u, 0x3F803F80u};
#pragma unroll
                    for (int mb = 0; mb < 4; mb++) {
                        uint32_t kf[4], vf[4], phi[8];
                        ldsm4(kf, sc + (mb * 16 + (lane & 15)) * 128 + (((2 * warp + (lane >> 4)) ^ (lane & 7)) << 4));
                        ldsm4t(vf, sc + 8192 + (mb * 16 + (lane >> 4) * 8 + (lane & 7)) * 128 + (((2 * warp + ((lane >> 3) & 1)) ^ (lane & 7)) << 4));
                        float p0[4] = {0.f, 0.f, 0.f, 0.f}, p1[4] = {0.f, 0.f, 0.f, 0.f};
                        mma16816(p0, kf, wf.x, wf.y);
                        mma16816(p1, kf, wf.z, wf.w);
                        feature_map(p0, p1, phi);
#pragma unroll
                        for (int fb = 0; fb < 4; fb++) {
                            const uint32_t b0 = movm(phi[2 * fb]), b1 = movm(phi[2 * fb + 1]);
                            mma16816(kv + 4 * fb, vf, b0, b1);
                            mma16816(zz + 4 * fb, ones, b0, b1);
                        }
                    }
                    fence_proxy_async();
                    __syncwarp();
                    c.release(slot);
                    float4* dst = g_kvpart + (head * 32 + tb * 2 + wgi) * 136;
#pragma unroll
                    for (int fb = 0; fb < 4; fb++) {
                        dst[fb * 32 + lane] = make_float4(kv[4 * fb], kv[4 * fb + 1], kv[4 * fb + 2], kv[4 * fb + 3]);
                        if (lane < 4) reinterpret_cast<float2*>(dst + 128)[fb * 4 + lane] = make_float2(zz[4 * fb], zz[4 * fb + 1]);
                    }
                    c.signal(0);
                }
                PROF(2);
#pragma unroll 1
                for (int i = 0; i < 12; i++) {
                    if (i == 0 || i == 4) c.load_tokens(a);
                    c.proj_tile(acc, a);
                    uint4* dst = i < 4 ? g_q + (4 * cg + i) * 32768 : ((i & 1) ? g_v : g_k) + (4 * cg + ((i - 4) >> 1)) * 32768;
                    store_tile(dst + tb * 2048, wgi * 64 + warp * 16, lane, acc, 1.f, 1.f);
                    c.signal(1 + i);
                }
            }
            PROF(3);
            {
                float o[64], s[64];
                uint32_t p[32], qf[32];
                float m0, m1, l0, l1;
                const int rsel = wgi == 0 ? 3 - rank : rank;
                const bool odd = rsel & 1;
                uint32_t pv_lo = 0, pv_hi = 8192;
                bool pv_dohi = true;
                int pv_acc = 1;
                uint4* odst = nullptr;
#pragma unroll
                for (int i = 0; i < 64; i++) o[i] = 0.f;
#pragma unroll
                for (int i = 0; i < 32; i++) p[i] = 0;
                m0 = m1 = l0 = l1 = 0.f;
#pragma unroll 1
                for (int it = 0; it < 4; it++) {
                    const int sb = item_block(it, tp);
                    uint32_t ks, vs, kb, vb = 0;
                    {
                        uint32_t slot;
                        const uint32_t qb = c.take(slot) + wgi * 16384 + (warp * 16 + (lane & 15)) * 128;
#pragma unroll
                        for (int k = 0; k < 8; k++)
                            ldsm4(qf + 4 * k, qb + (k >> 2) * 8192 + ((((k & 3) * 2 + (lane >> 4)) ^ (lane & 7)) << 4));
                        pin<32>(qf);
                        __syncwarp();
                        c.release(slot);
                    }
                    kb = c.take(ks);
                    if (it > 0) vb = c.take(vs);
                    if (wgi == 1) {
                        c.release(ks);
                        c.turn_wait();
                        if (it > 0) {
                            wg_fence();
                            issue_pv(o, p, vb, pv_lo, pv_hi, pv_dohi, pv_acc);
                            wg_commit();
                        }
                        c.turn_pass();
                        if (it > 0) {
                            wg_wait<0>();
                            pin<64>(o);
                            c.release(vs);
                            store_tile(odst, 0, lane, o, __fdividef(1.f, quad_sum(l0)), __fdividef(1.f, quad_sum(l1)));
                            c.signal(12 + it);
                        }
                        kb = c.take(ks);
                    }
                    c.turn_wait();
                    wg_fence();
#pragma unroll
                    for (int k = 0; k < 8; k++)
                        wgmma_rs_n64(s, qf + 4 * k, make_desc(kb + (odd ? 8192 : 0) + (k >> 2) * 16384 + (k & 3) * 32, 16, 1024), k != 0);
                    if (odd) {
#pragma unroll
                        for (int k = 0; k < 8; k++)
                            wgmma_rs_n64(s + 32, qf + 4 * k, make_desc(kb + (k >> 2) * 16384 + (k & 3) * 32, 16, 1024), k != 0);
                    }
                    wg_commit();
                    const bool tail_pv = wgi == 0 && it > 0;
                    if (tail_pv) issue_pv(o, p, vb, 0, 8192, true, 1);
                    wg_commit();
                    c.turn_pass();
                    wg_wait<1>();
                    pin<64>(s);
                    c.release(ks);
                    const float pl0 = l0, pl1 = l1;
                    {
                        const int r0 = warp * 16 + g - 2 * q;
#pragma unroll
                        for (int j = 0; j < 8; j++) {
                            if (8 * j > r0) s[4 * j] = -INFINITY;
                            if (8 * j + 1 > r0) s[4 * j + 1] = -INFINITY;
                            if (8 * j > r0 + 8) s[4 * j + 2] = -INFINITY;
                            if (8 * j + 1 > r0 + 8) s[4 * j + 3] = -INFINITY;
                        }
                        m0 = m1 = -INFINITY;
                        row_max<32>(s, m0, m1);
                        if (odd) row_max<32>(s + 32, m0, m1);
                        m0 = quad_max(m0);
                        m1 = quad_max(m1);
                        l0 = l1 = 0.f;
                        row_exp<32>(s, m0 * SM_SCALE, m1 * SM_SCALE, l0, l1);
                        if (odd) row_exp<32>(s + 32, m0 * SM_SCALE, m1 * SM_SCALE, l0, l1);
                    }
                    wg_wait<0>();
                    pin<64>(o);
                    pin<32>(p);
                    if (tail_pv) {
                        c.release(vs);
                        store_tile(odst, 0, lane, o, __fdividef(1.f, quad_sum(pl0)), __fdividef(1.f, quad_sum(pl1)));
                        c.signal(12 + it);
                    }
                    if (wgi == 1) {
                        c.take(vs);
                        c.release(vs);
                    }
                    pack_p(p, s);
                    pv_lo = odd ? 8192 : 0; pv_hi = 0; pv_dohi = odd; pv_acc = 0;
                    {
                        const int rb = 4 * sb + rsel;
                        odst = g_q + ((4 * cg + it) * 16 + (rb >> 1)) * 2048 + ((rb & 1) * 64 + warp * 16) * 8;
                    }
                    const int nfull = 2 * sb + 1 - wgi;
#pragma unroll 1
                    for (int t = 0; t < nfull; t++) {
                        kb = c.take(ks);
                        vb = c.take(vs);
                        c.turn_wait();
                        wg_fence();
#pragma unroll
                        for (int k = 0; k < 8; k++)
                            wgmma_rs_n128<0>(s, qf + 4 * k, make_desc(kb + (k >> 2) * 16384 + (k & 3) * 32, 16, 1024), k != 0);
                        wg_commit();
                        issue_pv(o, p, vb, pv_lo, pv_hi, pv_dohi, pv_acc);
                        wg_commit();
                        c.turn_pass();
                        pv_lo = 0; pv_hi = 8192; pv_dohi = true; pv_acc = 1;
                        wg_wait<1>();
                        pin<64>(s);
                        c.release(ks);
                        float n0 = m0, n1 = m1;
                        row_max<64>(s, n0, n1);
                        n0 = quad_max(n0);
                        n1 = quad_max(n1);
                        const float a0 = ex2((m0 - n0) * SM_SCALE), a1 = ex2((m1 - n1) * SM_SCALE);
                        m0 = n0; m1 = n1;
                        l0 *= a0; l1 *= a1;
                        row_exp<64>(s, n0 * SM_SCALE, n1 * SM_SCALE, l0, l1);
                        wg_wait<0>();
                        pin<64>(o);
                        pin<32>(p);
                        c.release(vs);
                        pack_p(p, s);
#pragma unroll
                        for (int j = 0; j < 16; j++) {
                            o[4 * j] *= a0; o[4 * j + 1] *= a0;
                            o[4 * j + 2] *= a1; o[4 * j + 3] *= a1;
                        }
                    }
                    PROF(4 + it);
                }
                uint32_t vs;
                const uint32_t vb = c.take(vs);
                c.turn_wait();
                wg_fence();
                issue_pv(o, p, vb, pv_lo, pv_hi, pv_dohi, pv_acc);
                wg_commit();
                if (wgi == 0) c.turn_pass();
                wg_wait<0>();
                pin<64>(o);
                c.release(vs);
                store_tile(odst, 0, lane, o, __fdividef(1.f, quad_sum(l0)), __fdividef(1.f, quad_sum(l1)));
                c.signal(16);
            }
            PROF(8);
            {
                float acc[128];
                uint32_t as, bs0, bs1 = 0;
#pragma unroll 1
                for (int n = 0; n < 8; n++) {
                    const uint32_t pas = as, pbs = bs1;
                    const uint32_t ab = c.take(as) + wgi * 8192;
                    const uint32_t b0 = c.take(bs0);
                    wg_fence();
#pragma unroll
                    for (int k = 0; k < 4; k++)
                        wgmma_ss_n256(acc, make_desc(ab + k * 32, 16, 1024), make_desc(b0 + k * 2048, 8192, 1024), (n | k) != 0);
                    wg_commit();
                    if (n > 0) { wg_wait<1>(); c.release(pas); c.release(pbs); }
                    const uint32_t b1 = c.take(bs1);
#pragma unroll
                    for (int k = 0; k < 4; k++)
                        wgmma_ss_n256(acc, make_desc(ab + 16384 + k * 32, 16, 1024), make_desc(b1 + k * 2048, 8192, 1024), 1);
                    wg_commit();
                    wg_wait<1>();
                    c.release(bs0);
                }
                wg_wait<0>();
                pin<128>(acc);
                PROF(9);
                const int ks = cg >> 1;
                const int cta0 = (tp + (cg & 1) * 8) * 2 + rank;
                const int t256 = wgi * 128 + warp * 32 + lane;
#pragma unroll
                for (int x = 0; x < 4; x++) {
                    if (x != ks) {
                        float4* dst = g_xch + ((cta0 + 32 * x) * 3 + (ks - (ks > x))) * 2048 + t256;
#pragma unroll
                        for (int j = 0; j < 8; j++)
                            __stcg(dst + j * 256, make_float4(acc[x * 32 + 4 * j], acc[x * 32 + 4 * j + 1], acc[x * 32 + 4 * j + 2], acc[x * 32 + 4 * j + 3]));
                    }
                }
#pragma unroll
                for (int x = 1; x < 4; x++) {
                    if (x == ks) {
#pragma unroll
                        for (int j = 0; j < 32; j++) acc[j] = acc[x * 32 + j];
                    }
                }
                fence_gpu();
                __syncwarp();
                if (lane < 4 && lane != ks) flag_add(&g_flags[(F_XCH + (cta0 + 32 * lane) * 8 + wgi * 4 + warp) * FLAG_STRIDE]);
                flag_wait(&g_flags[(F_XCH + (cta0 + 32 * ks) * 8 + wgi * 4 + warp) * FLAG_STRIDE], ep * 3);
                const float4* src = g_xch + (cta0 + 32 * ks) * 3 * 2048 + t256;
                float4 v[24];
#pragma unroll
                for (int j = 0; j < 24; j++) v[j] = __ldcg(src + j * 256);
#pragma unroll
                for (int j = 0; j < 8; j++) {
                    acc[4 * j] += (v[j].x + v[8 + j].x) + v[16 + j].x;
                    acc[4 * j + 1] += (v[j].y + v[8 + j].y) + v[16 + j].y;
                    acc[4 * j + 2] += (v[j].z + v[8 + j].z) + v[16 + j].z;
                    acc[4 * j + 3] += (v[j].w + v[8 + j].w) + v[16 + j].w;
                }
                uint4* orow = reinterpret_cast<uint4*>(prm.out + (size_t)(tb * 128 + wgi * 64 + warp * 16 + g) * 1024 + 512 + (cg & 1) * 256 + ks * 64) + q;
#pragma unroll
                for (int a = 0; a < 2; a++) {
                    const float* x = acc + a * 16;
                    orow[a * 4] = quad_transpose(pack2(x[0], x[1]), pack2(x[4], x[5]), pack2(x[8], x[9]), pack2(x[12], x[13]), q);
                    orow[a * 4 + 1024] = quad_transpose(pack2(x[2], x[3]), pack2(x[6], x[7]), pack2(x[10], x[11]), pack2(x[14], x[15]), q);
                }
            }
            PROF(10);
        } else {
            uint32_t a[128];
            float acc[64];
            uint4* spill = g_ospill + (blockIdx.x - 128) * 3 * 8 * 256 + wgi * 128 + warp * 32 + lane;
#pragma unroll 1
            for (int b = 0; b < 4; b++) {
                const int row = ((cl - 64) * 4 + b) * 256 + rank * 128 + wgi * 64 + warp * 16 + g;
                c.load_tokens(a);
#pragma unroll 1
                for (int i = 0; i < 4; i++) {
                    c.proj_tile(acc, a);
                    if (b == 0 && i == 0) flag_wait(&g_flags[F_TAB * FLAG_STRIDE], ep * 132);
#pragma unroll
                    for (int hh = 0; hh < 8; hh++) {
                        const uint4* tab = g_tab + (i * 8 + hh) * 128 + lane;
                        const uint4 wf = __ldcg(tab), k0 = __ldcg(tab + 32), k1 = __ldcg(tab + 64), zf = __ldcg(tab + 96);
                        const float* x = acc + hh * 8;
                        const uint32_t qa[4] = {pack2(x[0], x[1]), pack2(x[2], x[3]), pack2(x[4], x[5]), pack2(x[6], x[7])};
                        float p0[4] = {0.f, 0.f, 0.f, 0.f}, p1[4] = {0.f, 0.f, 0.f, 0.f};
                        mma16816(p0, qa, wf.x, wf.y);
                        mma16816(p1, qa, wf.z, wf.w);
                        uint32_t phi[8];
                        feature_map(p0, p1, phi);
                        float n0[4] = {0.f, 0.f, 0.f, 0.f}, n1[4] = {0.f, 0.f, 0.f, 0.f}, dn[4] = {0.f, 0.f, 0.f, 0.f};
                        mma16816(n0, phi, k0.x, k0.y);
                        mma16816(n1, phi, k0.z, k0.w);
                        mma16816(dn, phi, zf.x, zf.y);
                        mma16816(n0, phi + 4, k1.x, k1.y);
                        mma16816(n1, phi + 4, k1.z, k1.w);
                        mma16816(dn, phi + 4, zf.z, zf.w);
                        const float i0 = __fdividef(1.f, dn[0] + 1e-6f), i1 = __fdividef(1.f, dn[2] + 1e-6f);
                        const uint4 of = make_uint4(pack2(n0[0] * i0, n0[1] * i0), pack2(n0[2] * i1, n0[3] * i1),
                                                    pack2(n1[0] * i0, n1[1] * i0), pack2(n1[2] * i1, n1[3] * i1));
                        if (i < 3) {
                            spill[(i * 8 + hh) * 256] = of;
                        } else {
                            a[96 + hh * 4] = of.x; a[97 + hh * 4] = of.y; a[98 + hh * 4] = of.z; a[99 + hh * 4] = of.w;
                        }
                    }
                }
#pragma unroll
                for (int j = 0; j < 24; j++) {
                    const uint4 v = spill[j * 256];
                    a[4 * j] = v.x; a[4 * j + 1] = v.y; a[4 * j + 2] = v.z; a[4 * j + 3] = v.w;
                }
#pragma unroll 1
                for (int i = 0; i < 4; i++) {
                    c.proj_tile(acc, a);
                    uint4* orow = reinterpret_cast<uint4*>(prm.out + (size_t)row * 1024 + i * 128) + q;
#pragma unroll
                    for (int a4 = 0; a4 < 4; a4++) {
                        const float* x = acc + a4 * 16;
                        orow[a4 * 4] = quad_transpose(pack2(x[0], x[1]), pack2(x[4], x[5]), pack2(x[8], x[9]), pack2(x[12], x[13]), q);
                        orow[a4 * 4 + 1024] = quad_transpose(pack2(x[2], x[3]), pack2(x[6], x[7]), pack2(x[10], x[11]), pack2(x[14], x[15]), q);
                    }
                }
                PROF(1 + b);
            }
            if (wgi == 0) c.turn_wait();
            if (blockIdx.x == 131 && tid == 0) *(volatile unsigned*)&g_epoch = ep;
        }
    }
    asm volatile("barrier.cluster.arrive;\n barrier.cluster.wait;" ::: "memory");
}

typedef CUresult (*EncodeFn)(CUtensorMap*, CUtensorMapDataType, cuuint32_t, void*, const cuuint64_t*, const cuuint64_t*,
                             const cuuint32_t*, const cuuint32_t*, CUtensorMapInterleave, CUtensorMapSwizzle,
                             CUtensorMapL2promotion, CUtensorMapFloatOOBfill);

void encode(EncodeFn fn, CUtensorMap* m, const void* ptr, uint64_t cols, uint64_t rows, uint32_t box_rows) {
    cuuint64_t dims[2] = {cols, rows};
    cuuint64_t strides[1] = {cols * 2};
    cuuint32_t box[2] = {64, box_rows};
    cuuint32_t es[2] = {1, 1};
    fn(m, CU_TENSOR_MAP_DATA_TYPE_BFLOAT16, 2, const_cast<void*>(ptr), dims, strides, box, es, CU_TENSOR_MAP_INTERLEAVE_NONE,
       CU_TENSOR_MAP_SWIZZLE_128B, CU_TENSOR_MAP_L2_PROMOTION_L2_256B, CU_TENSOR_MAP_FLOAT_OOB_FILL_NONE);
}

}

extern "C" void kernel_launch(void* const* d_in, const int* in_sizes, int n_in, void* d_out, int out_size) {
    static EncodeFn fn = nullptr;
    if (!fn) {
        void* p = nullptr;
        cudaDriverEntryPointQueryResult st;
        cudaGetDriverEntryPoint("cuTensorMapEncodeTiled", &p, cudaEnableDefault, &st);
        fn = (EncodeFn)p;
        cudaFuncSetAttribute(fused_kernel, cudaFuncAttributeMaxDynamicSharedMemorySize, SMEM_BYTES);
    }
    Params prm;
    encode(fn, &prm.xA, d_in[0], 512, 2048, 128);
    encode(fn, &prm.wqkv, d_in[1], 1536, 512, 128);
    encode(fn, &prm.woA, d_in[3], 512, 512, 128);
    encode(fn, &prm.xB, d_in[4], 512, 2048, 128);
    encode(fn, &prm.ckv, d_in[5], 512, 2048, 128);
    encode(fn, &prm.wq, d_in[6], 4096, 512, 128);
    encode(fn, &prm.wuk, d_in[7], 4096, 512, 128);
    encode(fn, &prm.wuv, d_in[8], 4096, 512, 128);
    encode(fn, &prm.woB, d_in[9], 512, 4096, 64);
    prm.wphi = (const __nv_bfloat16*)d_in[2];
    prm.out = (__nv_bfloat16*)d_out;
    fused_kernel<<<132, 384, SMEM_BYTES, cudaStreamPerThread>>>(prm);
}
```

```cpp
#include <cuda.h>
#include <cuda_runtime.h>
#include <cuda_bf16.h>
#include <stdint.h>

namespace {

constexpr int NSLOT = 7;
constexpr int SLOT_BYTES = 32768;
constexpr int NSIG = 8;
constexpr int OFF_FULL = NSLOT * SLOT_BYTES;
constexpr int OFF_EMPTY = OFF_FULL + 64;
constexpr int OFF_SIG = OFF_EMPTY + 64;
constexpr int OFF_GATE = OFF_SIG + NSIG * 8;
constexpr int NGATE = 11;
constexpr int OFF_EPOCH = OFF_GATE + NGATE * 8;
constexpr int SMEM_USED = OFF_EPOCH + 8;
constexpr int SMEM_BYTES = SMEM_USED + 16 + 1024;

#define PF1 10
#define PF2 19
#define PF_KV 1
constexpr int FLAG_STRIDE = 8;
constexpr int F_HEAD = 0;
constexpr int F_CTX = F_HEAD + 16;
constexpr int F_AKV = F_CTX + 256;
constexpr int F_TAB = F_AKV + 8;
constexpr int F_OA = F_TAB + 1;
constexpr int F_TOTAL = F_OA + 16;

struct Params {
    CUtensorMap xA, wqkv, woA, xB, ckv, wq, wuk, wuv, woB;
    const __nv_bfloat16* wphi;
    __nv_bfloat16* out;
    uint32_t zero;
};

__device__ uint4 g_ctx[32 * 16 * 2048];
__device__ uint4 g_k[32 * 16 * 2048];
__device__ uint4 g_v[32 * 16 * 2048];
__device__ float4 g_kvpart[32 * 32 * 136];
__device__ uint4 g_tab[32 * 4 * 32];
__device__ uint4 g_oa[16 * 4 * 2048];
__device__ uint4 g_qa[4 * 16 * 8 * 256];
__device__ uint4 g_xch[128 * 3 * 4 * 256];
__device__ unsigned g_flags[F_TOTAL * FLAG_STRIDE];
__device__ unsigned g_epoch;
#define TR(c, id) do {} while (0)

__device__ __forceinline__ uint32_t smem_u32(const void* p) { return (uint32_t)__cvta_generic_to_shared(p); }
__device__ __forceinline__ void mbar_init(uint32_t bar, uint32_t cnt) {
    asm volatile("mbarrier.init.shared::cta.b64 [%0], %1;" ::"r"(bar), "r"(cnt) : "memory");
}
__device__ __forceinline__ void mbar_expect_tx(uint32_t bar, uint32_t bytes) {
    asm volatile("mbarrier.arrive.expect_tx.shared::cta.b64 _, [%0], %1;" ::"r"(bar), "r"(bytes) : "memory");
}
__device__ __forceinline__ void mbar_arrive(uint32_t bar) {
    asm volatile("mbarrier.arrive.shared::cta.b64 _, [%0];" ::"r"(bar) : "memory");
}
__device__ __forceinline__ void mbar_arrive_cluster(uint32_t bar) {
    asm volatile("mbarrier.arrive.shared::cluster.b64 _, [%0];" ::"r"(bar) : "memory");
}
__device__ __forceinline__ void mbar_wait(uint32_t bar, uint32_t parity) {
    asm volatile(
        "{\n .reg .pred p;\n .reg .u32 c;\n mov.u32 c, 0;\n"
        "W_LOOP:\n mbarrier.try_wait.parity.shared::cta.b64 p, [%0], %1;\n @p bra W_DONE;\n"
        " add.u32 c, c, 1;\n setp.lt.u32 p, c, 2000000;\n @p bra W_LOOP;\n trap;\n W_DONE:\n }"
        ::"r"(bar), "r"(parity) : "memory");
}
__device__ __forceinline__ void mbar_wait_idle(uint32_t bar, uint32_t parity) {
    asm volatile(
        "{\n .reg .pred p;\n .reg .u32 c;\n mov.u32 c, 0;\n"
        "W_LOOP:\n mbarrier.try_wait.parity.shared::cta.b64 p, [%0], %1, %2;\n @p bra W_DONE;\n"
        " add.u32 c, c, 1;\n setp.lt.u32 p, c, 200000;\n @p bra W_LOOP;\n trap;\n W_DONE:\n }"
        ::"r"(bar), "r"(parity), "n"(4000) : "memory");
}
__device__ __forceinline__ bool mbar_test(uint32_t bar, uint32_t parity) {
    uint32_t ok;
    asm volatile("{ .reg .pred p; mbarrier.test_wait.parity.shared::cta.b64 p, [%1], %2; selp.u32 %0, 1, 0, p; }"
                 : "=r"(ok) : "r"(bar), "r"(parity) : "memory");
    return ok;
}
__device__ __forceinline__ void flag_wait(const unsigned* p, unsigned target) {
    asm volatile(
        "{\n .reg .pred p;\n .reg .u32 c, v;\n .reg .s32 d;\n mov.u32 c, 0;\n"
        "F_LOOP:\n ld.relaxed.gpu.global.u32 v, [%0];\n sub.s32 d, v, %1;\n setp.ge.s32 p, d, 0;\n @p bra F_DONE;\n"
        " nanosleep.u32 200;\n add.u32 c, c, 1;\n setp.lt.u32 p, c, 4000000;\n @p bra F_LOOP;\n trap;\n F_DONE:\n fence.acquire.gpu;\n }"
        ::"l"(p), "r"(target) : "memory");
}
__device__ __forceinline__ void flag_add(unsigned* p) {
    asm volatile("red.relaxed.gpu.global.add.u32 [%0], 1;" ::"l"(p) : "memory");
}
__device__ __forceinline__ void fence_gpu() { asm volatile("fence.release.gpu;" ::: "memory"); }
__device__ __forceinline__ void fence_proxy_async() { asm volatile("fence.proxy.async.global;" ::: "memory"); }

__device__ __forceinline__ void bulk_load(uint32_t dst, const void* src, uint32_t bytes, uint32_t bar) {
    asm volatile("cp.async.bulk.shared::cluster.global.mbarrier::complete_tx::bytes [%0], [%1], %2, [%3];"
                 ::"r"(dst), "l"(src), "r"(bytes), "r"(bar) : "memory");
}
__device__ __forceinline__ void bulk_load_mc(uint32_t dst, const void* src, uint32_t bytes, uint32_t bar) {
    asm volatile("cp.async.bulk.shared::cluster.global.mbarrier::complete_tx::bytes.multicast::cluster [%0], [%1], %2, [%3], %4;"
                 ::"r"(dst), "l"(src), "r"(bytes), "r"(bar), "h"((uint16_t)3) : "memory");
}
__device__ __forceinline__ void tma_load(uint32_t dst, const CUtensorMap* m, int c0, int c1, uint32_t bar) {
    asm volatile("cp.async.bulk.tensor.2d.shared::cluster.global.mbarrier::complete_tx::bytes [%0], [%1, {%3, %4}], [%2];"
                 ::"r"(dst), "l"(m), "r"(bar), "r"(c0), "r"(c1) : "memory");
}
__device__ __forceinline__ void tma_load3(uint32_t dst, const CUtensorMap* m, int c1, int c2, uint32_t bar) {
    asm volatile("cp.async.bulk.tensor.3d.shared::cluster.global.mbarrier::complete_tx::bytes [%0], [%1, {0, %3, %4}], [%2];"
                 ::"r"(dst), "l"(m), "r"(bar), "r"(c1), "r"(c2) : "memory");
}
__device__ __forceinline__ void tma_load_mc(uint32_t dst, const CUtensorMap* m, int c0, int c1, uint32_t bar) {
    asm volatile("cp.async.bulk.tensor.2d.shared::cluster.global.mbarrier::complete_tx::bytes.multicast::cluster [%0], [%1, {%3, %4}], [%2], %5;"
                 ::"r"(dst), "l"(m), "r"(bar), "r"(c0), "r"(c1), "h"((uint16_t)3) : "memory");
}
__device__ __forceinline__ void prefetch_bulk(const void* src, uint32_t bytes) {
    asm volatile("cp.async.bulk.prefetch.L2.global [%0], %1;" ::"l"(src), "r"(bytes) : "memory");
}
__device__ __forceinline__ void prefetch_box(const CUtensorMap* m, int c0, int c1) {
    asm volatile("cp.async.bulk.prefetch.tensor.2d.L2.global [%0, {%1, %2}];" ::"l"(m), "r"(c0), "r"(c1) : "memory");
}
__device__ __forceinline__ void st_relaxed_128(uint4* p, uint32_t a, uint32_t b, uint32_t c, uint32_t d) {
    asm volatile("{ .reg .b128 v; .reg .b64 l, h; mov.b64 l, {%1, %2}; mov.b64 h, {%3, %4}; mov.b128 v, {l, h};\n"
                 "st.relaxed.gpu.global.b128 [%0], v; }" ::"l"(p), "r"(a), "r"(b), "r"(c), "r"(d) : "memory");
}
__device__ __forceinline__ void ld_relaxed_128(const uint4* p, uint32_t* r) {
    asm volatile("{ .reg .b128 v; .reg .b64 l, h; ld.relaxed.gpu.global.b128 v, [%4];\n"
                 "mov.b128 {l, h}, v; mov.b64 {%0, %1}, l; mov.b64 {%2, %3}, h; }"
                 : "=r"(r[0]), "=r"(r[1]), "=r"(r[2]), "=r"(r[3]) : "l"(p) : "memory");
}
__device__ __forceinline__ uint4 lds128(uint32_t addr) {
    uint4 v;
    asm("ld.shared.v4.b32 {%0, %1, %2, %3}, [%4];" : "=r"(v.x), "=r"(v.y), "=r"(v.z), "=r"(v.w) : "r"(addr));
    return v;
}
__device__ __forceinline__ uint32_t desc_lo(uint32_t addr, uint32_t lbo) { return ((addr & 0x3FFFF) >> 4) | ((lbo >> 4) << 16); }
constexpr uint32_t HI128 = 0x40000040u, HI64 = 0x80000020u;
#define DESC_HI "0x40000040"
__device__ __forceinline__ void wg_fence() { asm volatile("wgmma.fence.sync.aligned;" ::: "memory"); }
__device__ __forceinline__ void wg_commit() { asm volatile("wgmma.commit_group.sync.aligned;" ::: "memory"); }
template <int N> __device__ __forceinline__ void wg_wait() { asm volatile("wgmma.wait_group.sync.aligned %0;" ::"n"(N) : "memory"); }
template <int N> __device__ __forceinline__ void pin(float* a) {
#pragma unroll
    for (int i = 0; i < N; i++) asm volatile("" : "+f"(a[i])::"memory");
}
template <int N> __device__ __forceinline__ void pin(uint32_t* a) {
#pragma unroll
    for (int i = 0; i < N; i++) asm volatile("" : "+r"(a[i])::"memory");
}
__device__ __forceinline__ void bar_sync(int id, int n) { asm volatile("bar.sync %0, %1;" ::"r"(id), "r"(n) : "memory"); }
__device__ __forceinline__ void bar_arrive(int id, int n) { asm volatile("bar.arrive %0, %1;" ::"r"(id), "r"(n) : "memory"); }

#define R8(a, o) "+f"(a[o + 0]), "+f"(a[o + 1]), "+f"(a[o + 2]), "+f"(a[o + 3]), "+f"(a[o + 4]), "+f"(a[o + 5]), "+f"(a[o + 6]), "+f"(a[o + 7])
#define R32(a, o) R8(a, o), R8(a, o + 8), R8(a, o + 16), R8(a, o + 24)
#define R64(a, o) R32(a, o), R32(a, o + 32)
#define W8(a, o) "=f"(a[o + 0]), "=f"(a[o + 1]), "=f"(a[o + 2]), "=f"(a[o + 3]), "=f"(a[o + 4]), "=f"(a[o + 5]), "=f"(a[o + 6]), "=f"(a[o + 7])
#define W32(a, o) W8(a, o), W8(a, o + 8), W8(a, o + 16), W8(a, o + 24)
#define W64(a, o) W32(a, o), W32(a, o + 32)
#define L32 "%0,%1,%2,%3,%4,%5,%6,%7,%8,%9,%10,%11,%12,%13,%14,%15,%16,%17,%18,%19,%20,%21,%22,%23,%24,%25,%26,%27,%28,%29,%30,%31"
#define L64 L32 ",%32,%33,%34,%35,%36,%37,%38,%39,%40,%41,%42,%43,%44,%45,%46,%47,%48,%49,%50,%51,%52,%53,%54,%55,%56,%57,%58,%59,%60,%61,%62,%63"
#define L128 L64 ",%64,%65,%66,%67,%68,%69,%70,%71,%72,%73,%74,%75,%76,%77,%78,%79,%80,%81,%82,%83,%84,%85,%86,%87,%88,%89,%90,%91,%92,%93,%94,%95" \
    ",%96,%97,%98,%99,%100,%101,%102,%103,%104,%105,%106,%107,%108,%109,%110,%111,%112,%113,%114,%115,%116,%117,%118,%119,%120,%121,%122,%123,%124,%125,%126,%127"

template <int TB, uint32_t HI>
__device__ __forceinline__ void wgmma_rs_n128(float* d, const uint32_t* a, uint32_t db, int acc) {
    asm volatile("{ .reg .pred p; .reg .b64 b; setp.ne.b32 p, %69, 0; mov.b64 b, {%68, %71};\n"
                 "wgmma.mma_async.sync.aligned.m64n128k16.f32.bf16.bf16 {" L64 "}, {%64,%65,%66,%67}, b, p, 1, 1, %70; }"
                 : R64(d, 0) : "r"(a[0]), "r"(a[1]), "r"(a[2]), "r"(a[3]), "r"(db), "r"(acc), "n"(TB), "n"(HI));
}
__device__ __forceinline__ void wgmma_rs_n64(float* d, const uint32_t* a, uint32_t db) {
    asm volatile("{ .reg .b64 b; mov.b64 b, {%36, %37};\n"
                 "wgmma.mma_async.sync.aligned.m64n64k16.f32.bf16.bf16 {" L32 "}, {%32,%33,%34,%35}, b, 1, 1, 1, 0; }"
                 : R32(d, 0) : "r"(a[0]), "r"(a[1]), "r"(a[2]), "r"(a[3]), "r"(db), "n"(HI64));
}
template <int TB, uint32_t HI>
__device__ __forceinline__ void wgmma_rs_n128_set(float* d, const uint32_t* a, uint32_t db) {
    asm volatile("{ .reg .b64 b; mov.b64 b, {%68, %70};\n"
                 "wgmma.mma_async.sync.aligned.m64n128k16.f32.bf16.bf16 {" L64 "}, {%64,%65,%66,%67}, b, 0, 1, 1, %69; }"
                 : W64(d, 0) : "r"(a[0]), "r"(a[1]), "r"(a[2]), "r"(a[3]), "r"(db), "n"(TB), "n"(HI));
}
__device__ __forceinline__ void wgmma_rs_n64_set(float* d, const uint32_t* a, uint32_t db) {
    asm volatile("{ .reg .b64 b; mov.b64 b, {%36, %37};\n"
                 "wgmma.mma_async.sync.aligned.m64n64k16.f32.bf16.bf16 {" L32 "}, {%32,%33,%34,%35}, b, 0, 1, 1, 0; }"
                 : W32(d, 0) : "r"(a[0]), "r"(a[1]), "r"(a[2]), "r"(a[3]), "r"(db), "n"(HI64));
}
__device__ __forceinline__ void wgmma_ss_n256(float* d, uint32_t da, uint32_t db, int acc) {
    asm volatile("{ .reg .pred p; .reg .b64 a, b; setp.ne.b32 p, %130, 0; mov.b64 a, {%128, %131}; mov.b64 b, {%129, " DESC_HI "};\n"
                 "wgmma.mma_async.sync.aligned.m64n256k16.f32.bf16.bf16 {" L128 "}, a, b, p, 1, 1, 0, 1; }"
                 : R64(d, 0), R64(d, 64) : "r"(da), "r"(db), "r"(acc), "n"(HI64));
}
__device__ __forceinline__ void wgmma_ss_n128(float* d, uint32_t da, uint32_t db, int acc) {
    asm volatile("{ .reg .pred p; .reg .b64 a, b; setp.ne.b32 p, %66, 0; mov.b64 a, {%64, " DESC_HI "}; mov.b64 b, {%65, " DESC_HI "};\n"
                 "wgmma.mma_async.sync.aligned.m64n128k16.f32.bf16.bf16 {" L64 "}, a, b, p, 1, 1, 0, 1; }"
                 : R64(d, 0) : "r"(da), "r"(db), "r"(acc));
}
__device__ __forceinline__ void wgmma_ss_n128_set(float* d, uint32_t da, uint32_t db) {
    asm volatile("{ .reg .b64 a, b; mov.b64 a, {%64, " DESC_HI "}; mov.b64 b, {%65, " DESC_HI "};\n"
                 "wgmma.mma_async.sync.aligned.m64n128k16.f32.bf16.bf16 {" L64 "}, a, b, 0, 1, 1, 0, 1; }"
                 : W64(d, 0) : "r"(da), "r"(db));
}
__device__ __forceinline__ void wgmma_ss_n64(float* d, uint32_t da, uint32_t db, int acc) {
    asm volatile("{ .reg .pred p; .reg .b64 a, b; setp.ne.b32 p, %34, 0; mov.b64 a, {%32, " DESC_HI "}; mov.b64 b, {%33, " DESC_HI "};\n"
                 "wgmma.mma_async.sync.aligned.m64n64k16.f32.bf16.bf16 {" L32 "}, a, b, p, 1, 1, 0, 1; }"
                 : R32(d, 0) : "r"(da), "r"(db), "r"(acc));
}
__device__ __forceinline__ void mma16816(float* c, const uint32_t* a, uint32_t b0, uint32_t b1) {
    asm("mma.sync.aligned.m16n8k16.row.col.f32.bf16.bf16.f32 {%0,%1,%2,%3}, {%4,%5,%6,%7}, {%8,%9}, {%0,%1,%2,%3};"
                 : "+f"(c[0]), "+f"(c[1]), "+f"(c[2]), "+f"(c[3])
                 : "r"(a[0]), "r"(a[1]), "r"(a[2]), "r"(a[3]), "r"(b0), "r"(b1));
}
__device__ __forceinline__ void ldsm4(uint32_t* r, uint32_t addr) {
    asm volatile("ldmatrix.sync.aligned.m8n8.x4.shared.b16 {%0,%1,%2,%3}, [%4];"
                 : "=r"(r[0]), "=r"(r[1]), "=r"(r[2]), "=r"(r[3]) : "r"(addr) : "memory");
}
__device__ __forceinline__ void ldsm4t(uint32_t* r, uint32_t addr) {
    asm volatile("ldmatrix.sync.aligned.m8n8.x4.trans.shared.b16 {%0,%1,%2,%3}, [%4];"
                 : "=r"(r[0]), "=r"(r[1]), "=r"(r[2]), "=r"(r[3]) : "r"(addr) : "memory");
}
__device__ __forceinline__ void stsm4(uint32_t addr, uint32_t a, uint32_t b, uint32_t c, uint32_t d) {
    asm volatile("stmatrix.sync.aligned.m8n8.x4.shared.b16 [%0], {%1,%2,%3,%4};" ::"r"(addr), "r"(a), "r"(b), "r"(c), "r"(d) : "memory");
}
__device__ __forceinline__ uint32_t movm(uint32_t a) {
    uint32_t d;
    asm("movmatrix.sync.aligned.m8n8.trans.b16 %0, %1;" : "=r"(d) : "r"(a));
    return d;
}
__device__ __forceinline__ uint32_t pack2(float lo, float hi) {
    uint32_t d;
    asm("cvt.rn.bf16x2.f32 %0, %1, %2;" : "=r"(d) : "f"(hi), "f"(lo));
    return d;
}
__device__ __forceinline__ float ex2(float x) {
    float y;
    asm("ex2.approx.ftz.f32 %0, %1;" : "=f"(y) : "f"(x));
    return y;
}
__device__ __forceinline__ float rcp(float x) {
    float y;
    asm("rcp.approx.ftz.f32 %0, %1;" : "=f"(y) : "f"(x));
    return y;
}
__device__ __forceinline__ float quad_max(float v) {
    v = fmaxf(v, __shfl_xor_sync(~0u, v, 1));
    return fmaxf(v, __shfl_xor_sync(~0u, v, 2));
}
__device__ __forceinline__ float quad_sum(float v) {
    v += __shfl_xor_sync(~0u, v, 1);
    return v + __shfl_xor_sync(~0u, v, 2);
}
__device__ __forceinline__ uint4 quad_transpose(uint32_t r0, uint32_t r1, uint32_t r2, uint32_t r3, int q) {
    const bool b0 = q & 1, b1 = q & 2;
    uint32_t s0 = __shfl_xor_sync(~0u, b0 ? r0 : r1, 1), s1 = __shfl_xor_sync(~0u, b0 ? r2 : r3, 1);
    uint32_t t0 = b0 ? s0 : r0, t1 = b0 ? r1 : s0, t2 = b0 ? s1 : r2, t3 = b0 ? r3 : s1;
    s0 = __shfl_xor_sync(~0u, b1 ? t0 : t2, 2);
    s1 = __shfl_xor_sync(~0u, b1 ? t1 : t3, 2);
    return make_uint4(b1 ? s0 : t0, b1 ? s1 : t1, b1 ? t2 : s0, b1 ? t3 : s1);
}

struct Ring {
    uint32_t slot, phase;
    __device__ __forceinline__ void advance() {
        if (++slot == NSLOT) { slot = 0; phase ^= 1; }
    }
};

struct Producer {
    uint32_t base, rank;
    bool lead;
    Ring r;
    __device__ __forceinline__ uint32_t acquire(uint32_t bytes, uint32_t& bar, bool wait = true) {
                if (wait) mbar_wait_idle(base + OFF_EMPTY + 8 * r.slot, r.phase ^ 1);
        bar = base + OFF_FULL + 8 * r.slot;
        const uint32_t dst = base + r.slot * SLOT_BYTES;
        if (lead) {
            if (bytes) mbar_expect_tx(bar, bytes); else mbar_arrive(bar);
        }
        r.advance();
        return dst;
    }
    __device__ __forceinline__ void token_slot(const CUtensorMap* m, int s, int row0, bool wait = true) {
        uint32_t bar, dst = acquire(SLOT_BYTES, bar, wait);
        if (lead) {
            tma_load(dst, m, s * 128, row0, bar);
            tma_load(dst + 16384, m, s * 128 + 64, row0, bar);
        }
    }
    __device__ __forceinline__ void weight_slot(const CUtensorMap* m, int col, int s, bool wait = true) {
        uint32_t bar, dst = acquire(SLOT_BYTES, bar, wait);
        if (lead) tma_load_mc(dst + rank * 16384, m, col, s * 128, bar);
    }
    __device__ __forceinline__ void tokens(const CUtensorMap* m, int row0) {
#pragma unroll 1
        for (int s = 0; s < 4; s++) token_slot(m, s, row0);
    }
    __device__ __forceinline__ void wtile(const CUtensorMap* m, int col) {
#pragma unroll 1
        for (int s = 0; s < 4; s++) weight_slot(m, col, s);
    }
    __device__ __forceinline__ void gate(int i) { mbar_wait_idle(base + OFF_GATE + 8 * i, 0); }
    __device__ __forceinline__ void shared_tile(const uint4* src) {
        uint32_t bar, dst = acquire(SLOT_BYTES, bar);
        if (lead) bulk_load_mc(dst + rank * 16384, src + rank * 1024, 16384, bar);
    }
    __device__ __forceinline__ void private_tile(const uint4* src) {
        uint32_t bar, dst = acquire(SLOT_BYTES, bar);
        if (lead) bulk_load(dst, src, SLOT_BYTES, bar);
    }
};

struct Consumer {
    uint32_t base, empty_remote, zero;
    int wg, warp, lane;
    Ring r;
    __device__ __forceinline__ uint32_t take(uint32_t& slot) {
        slot = r.slot;
        mbar_wait(base + OFF_FULL + 8 * slot, r.phase);
        r.advance();
        return base + slot * SLOT_BYTES;
    }
    __device__ __forceinline__ bool peek2() {
        Ring n = r;
        const bool a = mbar_test(base + OFF_FULL + 8 * n.slot, n.phase);
        n.advance();
        return a & mbar_test(base + OFF_FULL + 8 * n.slot, n.phase);
    }
    __device__ __forceinline__ void take2(bool ready, uint32_t& s0, uint32_t& s1) {
        Ring n = r;
        n.advance();
        if (!__all_sync(~0u, ready)) {
            mbar_wait(base + OFF_FULL + 8 * r.slot, r.phase);
            mbar_wait(base + OFF_FULL + 8 * n.slot, n.phase);
        }
        s0 = r.slot; s1 = n.slot;
        n.advance();
        r = n;
    }
    __device__ __forceinline__ void take2(uint32_t& s0, uint32_t& s1) {
        take(s0);
        take(s1);
    }
    __device__ __forceinline__ void take1(bool ready, uint32_t& s0) {
        if (!__all_sync(~0u, ready)) mbar_wait(base + OFF_FULL + 8 * r.slot, r.phase);
        s0 = r.slot;
        r.advance();
    }
    __device__ __forceinline__ bool wg_any(bool v) {
        uint32_t any;
        asm volatile("{ .reg .pred p, q; setp.ne.u32 p, %1, 0; bar.red.or.pred q, %2, 128, p; selp.u32 %0, 1, 0, q; }"
                     : "=r"(any) : "r"((uint32_t)v), "r"(3 + wg) : "memory");
        return __any_sync(~0u, any);
    }
    __device__ __forceinline__ void release(uint32_t slot) {
        if (lane < 2) mbar_arrive_cluster(empty_remote + 8 * slot);
    }
    __device__ __forceinline__ void release_loaded(uint32_t slot, const uint32_t* a) {
        const uint32_t x = (a[0] ^ a[4] ^ a[8]) ^ (a[12] ^ a[16] ^ a[20]) ^ (a[24] ^ a[28]);
        if (lane < 2) mbar_arrive_cluster(empty_remote + 8 * slot + (x & zero));
    }
    __device__ __forceinline__ void order_after(float v) {
        asm volatile("{ .reg .pred p; setp.gt.f32 p, %0, 0f7F000000; @p st.shared.u32 [%1], %1; }"
                     ::"f"(v), "r"(base + SMEM_USED) : "memory");
    }
    __device__ __forceinline__ void turn_wait() { bar_sync(1 + wg, 256); }
    __device__ __forceinline__ void turn_pass() { bar_arrive(2 - wg, 256); }
    __device__ __forceinline__ void signal(int ev) {
        __syncwarp();
        if (lane == 0) mbar_arrive(base + OFF_SIG + ev * 8);
    }
    template <int S0, int S1>
    __device__ __forceinline__ void load_tokens(uint32_t* a) {
        const uint32_t row = wg * 64 + warp * 16 + (lane & 15);
        uint32_t slot[4];
#pragma unroll
        for (int s = S0; s < S1; s++) {
            const uint32_t sb = take(slot[s]);
#pragma unroll
            for (int k = 0; k < 8; k++)
                ldsm4(a + (s * 8 + k) * 4, sb + (k >> 2) * 16384 + row * 128 + ((((k & 3) * 2 + (lane >> 4)) ^ (lane & 7)) << 4));
            if (s > S0) release_loaded(slot[s - 1], a + (s - 1) * 32);
        }
        release_loaded(slot[S1 - 1], a + (S1 - 1) * 32);
    }
    template <bool FIRST, bool OWN>
    __device__ __forceinline__ void stream_chunk(float* acc, uint32_t ts, uint32_t ws) {
        const uint32_t da = desc_lo(base + ts * SLOT_BYTES + wg * (OWN ? 16384 : 8192), 16);
        const uint32_t db = desc_lo(base + ws * SLOT_BYTES, 16384);
        wg_fence();
#pragma unroll
        for (int k = 0; k < 8; k++) {
            if (FIRST && k == 0) wgmma_ss_n128_set(acc, da, db);
            else wgmma_ss_n128(acc, da + (k >> 2) * (OWN ? 512 : 1024) + (k & 3) * 2, db + k * 128, 1);
        }
        wg_commit();
    }
    __device__ __forceinline__ void first_tile(float* acc) {
#pragma unroll
        for (int s = 0; s < 4; s++) {
            uint32_t ts, ws;
            take2(ts, ws);
            TR(*this, 70);
            turn_wait();
            if (s == 0) stream_chunk<true, false>(acc, ts, ws);
            else stream_chunk<false, false>(acc, ts, ws);
            turn_pass();
            wg_wait<0>();
            release(ts);
            release(ws);
        }
        pin<64>(acc);
    }
    __device__ __forceinline__ void proj_tile(float* acc, uint32_t* a) {
        uint32_t slot, prev = 0;
        TR(*this, 1);
        uint32_t sb = take(slot);
        turn_wait();
#pragma unroll
        for (int s = 0; s < 4; s++) {
            if (s > 0) sb = take(slot);
            const uint32_t db = desc_lo(sb, 16384);
            wg_fence();
#pragma unroll
            for (int k = 0; k < 8; k++) {
                if ((s | k) == 0) wgmma_rs_n128_set<1, HI128>(acc, a, db);
                else wgmma_rs_n128<1, HI128>(acc, a + (s * 8 + k) * 4, db + k * 128, 1);
            }
            wg_commit();
            if (s == 3) turn_pass();
            if (s > 0) { wg_wait<1>(); release(prev); }
            prev = slot;
        }
        wg_wait<0>();
        pin<64>(acc);
        pin<128>(a);
        release(prev);
        TR(*this, 5);
    }
};

template <int A0 = 0, int A1 = 4>
__device__ __forceinline__ void store_tile(uint4* tile, int lane, const float* acc, float s0, float s1) {
    const int g = lane >> 2, q = lane & 3;
#pragma unroll
    for (int a = A0; a < A1; a++) {
        const float* c = acc + a * 16;
        uint4* p = tile + a * 512 + g * 4 + (q ^ (g >> 1));
        p[0] = make_uint4(pack2(c[0] * s0, c[1] * s0), pack2(c[4] * s0, c[5] * s0), pack2(c[8] * s0, c[9] * s0), pack2(c[12] * s0, c[13] * s0));
        p[32] = make_uint4(pack2(c[2] * s1, c[3] * s1), pack2(c[6] * s1, c[7] * s1), pack2(c[10] * s1, c[11] * s1), pack2(c[14] * s1, c[15] * s1));
    }
}
__device__ __forceinline__ uint32_t pack2v(float lo, float hi) {
    uint32_t d;
    asm("mul.rn.bf16x2 %0, %1, %2;" : "=r"(d) : "r"(pack2(lo, hi)), "r"(0x50805080u));
    return d;
}
__device__ __forceinline__ void store_tile_v(uint4* tile, int lane, const float* acc) {
    const int g = lane >> 2, q = lane & 3;
#pragma unroll
    for (int a = 0; a < 4; a++) {
        const float* c = acc + a * 16;
        uint4* p = tile + a * 512 + g * 4 + (q ^ (g >> 1));
        p[0] = make_uint4(pack2v(c[0], c[1]), pack2v(c[4], c[5]), pack2v(c[8], c[9]), pack2v(c[12], c[13]));
        p[32] = make_uint4(pack2v(c[2], c[3]), pack2v(c[6], c[7]), pack2v(c[10], c[11]), pack2v(c[14], c[15]));
    }
}
__device__ __forceinline__ void store_tile_natural(uint4* tile, int lane, const float* acc) {
    const int g = lane >> 2, q = lane & 3;
#pragma unroll
    for (int a = 0; a < 4; a++) {
        const float* c = acc + a * 16;
        uint4* p = tile + a * 512 + g * 4 + (q ^ (g >> 1));
        p[0] = quad_transpose(pack2(c[0], c[1]), pack2(c[4], c[5]), pack2(c[8], c[9]), pack2(c[12], c[13]), q);
        p[32] = quad_transpose(pack2(c[2], c[3]), pack2(c[6], c[7]), pack2(c[10], c[11]), pack2(c[14], c[15]), q);
    }
}
__device__ __forceinline__ void store_out64(__nv_bfloat16* out, uint32_t stage, int lane, const float* acc) {
#pragma unroll
    for (int k = 0; k < 4; k++) {
        const float* x = acc + k * 8;
        stsm4(stage + (lane & 15) * 128 + (((2 * k + (lane >> 4)) ^ (lane & 7)) << 4),
              pack2(x[0], x[1]), pack2(x[2], x[3]), pack2(x[4], x[5]), pack2(x[6], x[7]));
    }
    __syncwarp();
    uint4* orow = reinterpret_cast<uint4*>(out + (size_t)(lane >> 3) * 1024) + (lane & 7);
#pragma unroll
    for (int e = 0; e < 4; e++) {
        uint4 v;
        const uint32_t row = e * 4 + (lane >> 3);
        asm volatile("ld.shared.v4.b32 {%0, %1, %2, %3}, [%4];"
                     : "=r"(v.x), "=r"(v.y), "=r"(v.z), "=r"(v.w) : "r"(stage + row * 128 + (((lane ^ row) & 7) << 4)) : "memory");
        orow[e * 512] = v;
    }
}

constexpr float LOG2E = 1.4426950408889634f;

__device__ __forceinline__ void feature_range4(const float* p, float* mx, float* mn) {
#pragma unroll
    for (int r = 0; r < 8; r++) {
        const float* x = p + (r >> 1) * 8 + (r & 1) * 2;
        mx[r] = fmaxf(fmaxf(x[0], x[1]), fmaxf(x[4], x[5]));
        mn[r] = fminf(fminf(x[0], x[1]), fminf(x[4], x[5]));
    }
#pragma unroll
    for (int d = 1; d <= 2; d++) {
#pragma unroll
        for (int r = 0; r < 8; r++) {
            mx[r] = fmaxf(mx[r], __shfl_xor_sync(~0u, mx[r], d));
            mn[r] = fminf(mn[r], __shfl_xor_sync(~0u, mn[r], d));
        }
    }
}
template <bool NORM>
__device__ __forceinline__ void feature_map4(const float* p, const float* mx, const float* mn, uint32_t* phi) {
    float e[64];
#pragma unroll
    for (int r = 0; r < 8; r++) {
        const float* x = p + (r >> 1) * 8 + (r & 1) * 2;
        const float a = mx[r] * LOG2E, b = mn[r] * LOG2E;
#pragma unroll
        for (int i = 0; i < 4; i++) {
            const float v = x[(i >> 1) * 4 + (i & 1)];
            e[8 * r + i] = ex2(fmaf(v, LOG2E, -a));
            e[8 * r + 4 + i] = ex2(fmaf(v, -LOG2E, b));
        }
    }
    if (NORM) {
        float sum[16];
#pragma unroll
        for (int r = 0; r < 16; r++) sum[r] = (e[4 * r] + e[4 * r + 1]) + (e[4 * r + 2] + e[4 * r + 3]);
#pragma unroll
        for (int d = 1; d <= 2; d++) {
#pragma unroll
            for (int r = 0; r < 16; r++) sum[r] += __shfl_xor_sync(~0u, sum[r], d);
        }
#pragma unroll
        for (int r = 0; r < 16; r++) {
            const float w = rcp(sum[r]);
#pragma unroll
            for (int i = 0; i < 4; i++) e[4 * r + i] *= w;
        }
    }
#pragma unroll
    for (int r = 0; r < 8; r++) {
#pragma unroll
        for (int fb = 0; fb < 4; fb++) phi[(r >> 1) * 8 + 2 * fb + (r & 1)] = pack2(e[8 * r + 2 * fb], e[8 * r + 2 * fb + 1]);
    }
}

__device__ __forceinline__ uint4 wphi_load(const __nv_bfloat16* wphi, int head, int lane) {
    const uint32_t* w = reinterpret_cast<const uint32_t*>(wphi) + head * 128 + (lane >> 2) * 8 + (lane & 3);
    return make_uint4(__ldg(w), __ldg(w + 64), __ldg(w + 4), __ldg(w + 68));
}
__device__ __forceinline__ uint4 wphi_frags(uint4 w) { return make_uint4(movm(w.x), movm(w.y), movm(w.z), movm(w.w)); }

#define PROF(i) do {} while (0)
#define PROFT(i) do {} while (0)

constexpr float SM_SCALE = 0.08838834764831845f * LOG2E;

template <int N>
__device__ __forceinline__ void row_max(const float* s, float& m0, float& m1) {
#pragma unroll
    for (int j = 0; j < N / 4; j++) {
        m0 = fmaxf(m0, fmaxf(s[4 * j], s[4 * j + 1]));
        m1 = fmaxf(m1, fmaxf(s[4 * j + 2], s[4 * j + 3]));
    }
}
template <int N>
__device__ __forceinline__ void row_exp(float* s, float mc0, float mc1, float& l0, float& l1) {
#pragma unroll
    for (int j = 0; j < N / 4; j++) {
        s[4 * j] = ex2(fmaf(s[4 * j], SM_SCALE, -mc0));
        s[4 * j + 1] = ex2(fmaf(s[4 * j + 1], SM_SCALE, -mc0));
        s[4 * j + 2] = ex2(fmaf(s[4 * j + 2], SM_SCALE, -mc1));
        s[4 * j + 3] = ex2(fmaf(s[4 * j + 3], SM_SCALE, -mc1));
        l0 += s[4 * j] + s[4 * j + 1];
        l1 += s[4 * j + 2] + s[4 * j + 3];
    }
}
__device__ __forceinline__ void pack_p(uint32_t* p, const float* s) {
#pragma unroll
    for (int i = 0; i < 32; i++) p[i] = pack2(s[2 * i], s[2 * i + 1]);
}
__device__ __forceinline__ void issue_pv(float* o, const uint32_t* p, uint32_t vb, int acc) {
    const uint32_t db = desc_lo(vb, 8192);
#pragma unroll
    for (int k = 0; k < 8; k++) wgmma_rs_n128<1, HI64>(o, p + 4 * k, db + k * 64, k ? 1 : acc);
}
__device__ __forceinline__ void issue_qk(float* s, const uint32_t* qf, uint32_t kb) {
    const uint32_t db = desc_lo(kb, 16);
    wgmma_rs_n128_set<0, HI64>(s, qf, db);
#pragma unroll
    for (int k = 1; k < 8; k++) wgmma_rs_n128<0, HI64>(s, qf + 4 * k, db + (k >> 1) * 512 + (k & 1) * 2, 1);
}

constexpr float REF_BIAS = 91.f;
constexpr float V_SCALE = 0x1p34f, V_UNSCALE = 0x1p-34f;
constexpr float P_LIMIT = 0x1p49f;
struct AttnState {
    float o[64];
    uint32_t p[32], qf[32];
    float m0, m1, l0, l1;
    uint4* odst;
    uint32_t ks;
    bool ready;
};

__device__ __forceinline__ void item_head(Consumer& c, AttnState& st, bool pv, bool trail, int acc, int ev) {
    float s[64];
    uint32_t vs = 0, t0, w0, t1, w1;
    TR(c, 20);
    c.take2(st.ready, t0, w0);
    c.turn_wait();
    c.stream_chunk<true, true>(s, t0, w0);
    if (pv) {
        issue_pv(st.o, st.p, c.take(vs), acc);
        wg_commit();
        c.turn_pass();
        wg_wait<1>();
        c.release(t0);
        c.release(w0);
    } else {
        c.turn_pass();
    }
    TR(c, 21);
    c.take2(t1, w1);
    const float i0 = pv ? rcp(quad_sum(st.l0)) * V_UNSCALE : V_SCALE;
    const float i1 = pv ? rcp(quad_sum(st.l1)) * V_UNSCALE : V_SCALE;
    wg_wait<0>();
    pin<64>(st.o);
    pin<32>(st.p);
    if (pv) {
        c.release(vs);
        if (!trail) {
            store_tile(st.odst, c.lane, st.o, i0, i1);
            c.signal(ev);
        }
    } else {
        c.release(t0);
        c.release(w0);
    }
    TR(c, 60);
    c.turn_wait();
    c.stream_chunk<false, true>(s, t1, w1);
    c.turn_pass();
    TR(c, 61);
    if (trail) store_tile<0, 2>(st.odst, c.lane, st.o, i0, i1);
    c.take2(t0, w0);
    TR(c, 62);
    wg_wait<0>();
    c.release(t1);
    c.release(w1);
    if (trail) {
        store_tile<2, 4>(st.odst, c.lane, st.o, i0, i1);
        c.signal(ev);
    }
    c.turn_wait();
    c.stream_chunk<false, true>(s, t0, w0);
    if (trail) c.turn_pass();
    TR(c, 63);
    c.take2(t1, w1);
    TR(c, 64);
    if (trail) c.turn_wait();
    c.stream_chunk<false, true>(s, t1, w1);
    if (!trail) c.turn_pass();
    TR(c, 65);
    wg_wait<1>();
    c.release(t0);
    c.release(w0);
    c.take(st.ks);
    if (trail) {
        uint32_t skip;
        c.release(st.ks);
        c.take2(skip, st.ks);
        c.release(skip);
    }
    wg_wait<0>();
    pin<64>(s);
    c.release(t1);
    c.release(w1);
    pack_p(st.qf, s);
    TR(c, 23);
}

template <bool ODD>
__device__ __forceinline__ void diag_turn(Consumer& c, AttnState& st, bool trail) {
    constexpr int N = ODD ? 64 : 32;
    float s[N];
    const uint32_t ks = st.ks;
    const uint32_t db = desc_lo(c.base + ks * SLOT_BYTES, 16);
    if (!trail) c.turn_wait();
    wg_fence();
#pragma unroll
    for (int hf = 0; hf < N / 32; hf++) {
        wgmma_rs_n64_set(s + 32 * hf, st.qf, db + 256 * hf);
#pragma unroll
        for (int k = 1; k < 8; k++) wgmma_rs_n64(s + 32 * hf, st.qf + 4 * k, db + 256 * hf + (k >> 1) * 512 + (k & 1) * 2);
        wg_commit();
    }
    c.turn_pass();
    TR(c, 24);
    float m0 = -INFINITY, m1 = -INFINITY;
    if (ODD) {
        wg_wait<1>();
        pin<32>(s);
        row_max<16>(s, m0, m1);
        m0 = quad_max(m0);
        m1 = quad_max(m1);
        c.order_after(m0 + m1);
    }
    wg_wait<0>();
    pin<32>(s + N - 32);
    c.release(ks);
    TR(c, 25);
    st.ready = c.peek2();
    const int r0 = c.warp * 16 + (c.lane >> 2) - 2 * (c.lane & 3);
    float* tri = s + N - 32;
#pragma unroll
    for (int j = 0; j < 8; j++) {
        if (8 * j > r0) tri[4 * j] = -INFINITY;
        if (8 * j + 1 > r0) tri[4 * j + 1] = -INFINITY;
        if (8 * j > r0 + 8) tri[4 * j + 2] = -INFINITY;
        if (8 * j + 1 > r0 + 8) tri[4 * j + 3] = -INFINITY;
    }
    if (!ODD) {
        row_max<16>(s, m0, m1);
        m0 = quad_max(m0);
        m1 = quad_max(m1);
    }
#pragma unroll 1
    for (int pass = 0;; pass++) {
        st.m0 = fmaf(m0, SM_SCALE, REF_BIAS);
        st.m1 = fmaf(m1, SM_SCALE, REF_BIAS);
        st.l0 = st.l1 = 0.f;
#pragma unroll
        for (int j = 0; j < N / 4; j++) {
            const float e0 = ex2(fmaf(s[4 * j], SM_SCALE, -st.m0)), e1 = ex2(fmaf(s[4 * j + 1], SM_SCALE, -st.m0));
            const float e2 = ex2(fmaf(s[4 * j + 2], SM_SCALE, -st.m1)), e3 = ex2(fmaf(s[4 * j + 3], SM_SCALE, -st.m1));
            st.l0 += e0 + e1;
            st.l1 += e2 + e3;
            st.p[2 * j] = pack2(e0, e1);
            st.p[2 * j + 1] = pack2(e2, e3);
        }
        if (pass || !__any_sync(~0u, !(st.l0 + st.l1 <= P_LIMIT))) break;
        row_max<N>(s, m0, m1);
        m0 = quad_max(m0);
        m1 = quad_max(m1);
    }
#pragma unroll
    for (int i = N / 2; i < 32; i++) st.p[i] = 0u;
    TR(c, 27);
}

__device__ __forceinline__ void full_turn(Consumer& c, AttnState& st, int acc, bool yield) {
    float s[64];
    uint32_t ks, vs;
    c.take2(st.ready, vs, ks);
    const uint32_t kb = c.base + ks * SLOT_BYTES;
    c.turn_wait();
    wg_fence();
    issue_qk(s, st.qf, kb);
    wg_commit();
    issue_pv(st.o, st.p, c.base + vs * SLOT_BYTES, acc);
    wg_commit();
    c.turn_pass();
    TR(c, 13);
    if (yield) wg_wait<0>();
    wg_wait<1>();
    pin<64>(s);
    float t0 = 0.f, t1 = 0.f;
    row_exp<32>(s, st.m0, st.m1, t0, t1);
    c.order_after(t0 + t1);
    wg_wait<0>();
    pin<64>(st.o);
    pin<32>(st.p);
    c.release(vs);
    st.ready = c.peek2();
    row_exp<32>(s + 32, st.m0, st.m1, t0, t1);
    pack_p(st.p, s);
    if (c.wg_any(!(t0 + t1 <= P_LIMIT))) {
        float r[64];
        wg_fence();
        issue_qk(r, st.qf, kb);
        wg_commit();
        wg_wait<0>();
        pin<64>(r);
        float n0 = -INFINITY, n1 = -INFINITY;
        row_max<64>(r, n0, n1);
        n0 = fmaxf(fmaf(quad_max(n0), SM_SCALE, REF_BIAS), st.m0);
        n1 = fmaxf(fmaf(quad_max(n1), SM_SCALE, REF_BIAS), st.m1);
        const float a0 = ex2(0.5f * (st.m0 - n0)), a1 = ex2(0.5f * (st.m1 - n1));
        st.m0 = n0; st.m1 = n1;
        st.l0 = st.l0 * a0 * a0; st.l1 = st.l1 * a1 * a1;
        row_exp<64>(r, n0, n1, st.l0, st.l1);
        pack_p(st.p, r);
#pragma unroll
        for (int j = 0; j < 16; j++) {
            st.o[4 * j] = st.o[4 * j] * a0 * a0; st.o[4 * j + 1] = st.o[4 * j + 1] * a0 * a0;
            st.o[4 * j + 2] = st.o[4 * j + 2] * a1 * a1; st.o[4 * j + 3] = st.o[4 * j + 3] * a1 * a1;
        }
    } else {
        st.l0 += t0; st.l1 += t1;
    }
    c.release(ks);
}

__device__ __forceinline__ int item_block(int it, int tp) {
    const int u = (tp + 4 * ((it ^ (it >> 1)) & 1)) & 7;
    return (it & 2) ? 7 - u : u;
}
__device__ __forceinline__ int item_head_index(int it) { return (0x0132 >> (4 * it)) & 3; }
__device__ __forceinline__ int oproj_head(int ks, int n) { return 8 * ks + (n & 1) * 4 + item_head_index(n >> 1); }

__global__ void __cluster_dims__(2, 1, 1) __launch_bounds__(384, 1)
fused_kernel(const __grid_constant__ Params prm) {
    extern __shared__ uint8_t smem_raw[];
    const uint32_t base = (smem_u32(smem_raw) + 1023) & ~1023u;
    const int tid = threadIdx.x;
    const int wgi = __shfl_sync(~0u, tid >> 7, 0);
    const int warp = __shfl_sync(~0u, (tid >> 5) & 3, 0);
    const int lane = tid & 31;
    const uint32_t rank = blockIdx.x & 1;
    const int cl = blockIdx.x >> 1;
    const bool extra = cl >= 64;
    const int tp = cl & 7, cg = cl >> 3;

    if (tid == 256) {
        asm volatile("prefetch.tensormap [%0];" ::"l"(&prm.xA) : "memory");
#pragma unroll
        for (int i = 0; i < NSLOT; i++) {
            mbar_init(base + OFF_FULL + 8 * i, 1);
            mbar_init(base + OFF_EMPTY + 8 * i, 16);
        }
        asm volatile("fence.mbarrier_init.release.cluster;" ::: "memory");
    } else if (tid == 288) {
        asm volatile("prefetch.tensormap [%0];" ::"l"(&prm.wqkv) : "memory");
        for (int i = 0; i < NSIG; i++) mbar_init(base + OFF_SIG + 8 * i, 8);
        for (int i = 0; i < NGATE; i++) mbar_init(base + OFF_GATE + 8 * i, 1);
        asm volatile("fence.mbarrier_init.release.cluster;" ::: "memory");
    }
    __syncwarp();
    asm volatile("barrier.cluster.arrive.relaxed.aligned;" ::: "memory");

    if (wgi < 2) {
        asm volatile("setmaxnreg.inc.sync.aligned.u32 232;");
        asm volatile("barrier.cluster.wait.aligned;" ::: "memory");
        Consumer c;
        c.base = base; c.zero = prm.zero; c.wg = wgi; c.warp = warp; c.lane = lane; c.r = {0, 0};
        asm("mapa.shared::cluster.u32 %0, %1, %2;" : "=r"(c.empty_remote) : "r"(base + OFF_EMPTY), "r"(lane & 1));
        auto epoch = [&]() {
            uint32_t e;
            asm volatile("ld.shared.u32 %0, [%1];" : "=r"(e) : "r"(base + OFF_EPOCH) : "memory");
            return e;
        };
        if (wgi == 1) bar_arrive(1, 256);
        PROF(0);
        TR(c, 69);
        PROFT(30);

        if (!extra) {
            const int tb = tp * 2 + rank;
            uint32_t a[128];
            {
                float acc[64];
                const int head = 4 * cg + warp;
                uint4 wf = wphi_load(prm.wphi, head, lane);
                c.first_tile(acc);
                pin<4>(&wf.x);
                wf = wphi_frags(wf);
                PROF(1);
                TR(c, 72);
                {
                    uint32_t slot;
                    const uint32_t sc = c.take(slot) + wgi * 16384;
                    const uint32_t srow = warp * 16 + (lane & 15);
#pragma unroll
                    for (int jj = 0; jj < 8; jj++) {
                        const float* x = acc + jj * 8;
                        stsm4(sc + (jj >> 2) * 8192 + srow * 128 + ((((jj & 3) * 2 + (lane >> 4)) ^ (lane & 7)) << 4),
                              pack2(x[0], x[1]), pack2(x[2], x[3]), pack2(x[4], x[5]), pack2(x[6], x[7]));
                    }
                    asm volatile("fence.proxy.async.shared::cta;" ::: "memory");
                    bar_sync(3 + wgi, 128);
                    uint32_t f[32];
#pragma unroll
                    for (int mb = 0; mb < 4; mb++) {
                        ldsm4(f + mb * 8, sc + (mb * 16 + (lane & 15)) * 128 + (((2 * warp + (lane >> 4)) ^ (lane & 7)) << 4));
                        ldsm4t(f + mb * 8 + 4, sc + 8192 + (mb * 16 + (lane >> 4) * 8 + (lane & 7)) * 128 + (((2 * warp + ((lane >> 3) & 1)) ^ (lane & 7)) << 4));
                    }
                    c.release_loaded(slot, f);
                    float kv[16], zz[16];
#pragma unroll
                    for (int i = 0; i < 16; i++) { kv[i] = 0.f; zz[i] = 0.f; }
                    const uint32_t ones[4] = {0x3F803F80u, 0x3F803F80u, 0x3F803F80u, 0x3F803F80u};
                    float pk[32];
                    uint32_t phi[32];
#pragma unroll
                    for (int i = 0; i < 32; i++) pk[i] = 0.f;
#pragma unroll
                    for (int mb = 0; mb < 4; mb++) {
                        mma16816(pk + mb * 8, f + mb * 8, wf.x, wf.y);
                        mma16816(pk + mb * 8 + 4, f + mb * 8, wf.z, wf.w);
                    }
                    float mx[8], mn[8];
                    feature_range4(pk, mx, mn);
                    feature_map4<true>(pk, mx, mn, phi);
#pragma unroll
                    for (int mb = 0; mb < 4; mb++) {
#pragma unroll
                        for (int fb = 0; fb < 4; fb++) {
                            const uint32_t b0 = movm(phi[8 * mb + 2 * fb]), b1 = movm(phi[8 * mb + 2 * fb + 1]);
                            mma16816(kv + 4 * fb, f + mb * 8 + 4, b0, b1);
                            mma16816(zz + 4 * fb, ones, b0, b1);
                        }
                    }
                    TR(c, 73);
                    c.load_tokens<0, 1>(a);
                    if (wgi == 1) bar_sync(5, 256);
                    c.load_tokens<1, 4>(a);
                    if (wgi == 0) bar_arrive(5, 256);
                    float4* dst = g_kvpart + (head * 32 + tb * 2 + wgi) * 136;
#pragma unroll
                    for (int fb = 0; fb < 4; fb++) {
                        dst[fb * 32 + lane] = make_float4(kv[4 * fb], kv[4 * fb + 1], kv[4 * fb + 2], kv[4 * fb + 3]);
                        if (lane < 4) reinterpret_cast<float2*>(dst + 128)[fb * 4 + lane] = make_float2(zz[4 * fb], zz[4 * fb + 1]);
                    }
                }
                c.signal(0);
                PROF(2);
            }
            AttnState st;
#pragma unroll 1
            for (int i = 0; i < 8; i++) {
                c.proj_tile(st.o, a);
                st.odst = ((i & 1) ? g_v : g_k) + ((4 * cg + (i >> 1)) * 16 + tb) * 2048 + (wgi * 64 + warp * 16) * 4;
                if (i == 7 && wgi == 1) break;
                if (i & 1) store_tile_v(st.odst, lane, st.o);
                else store_tile_natural(st.odst, lane, st.o);
                if (i == 5 || i == 7) c.signal((i - 3) >> 1);
            }
            PROF(3);
            int pv_acc = 0;
#pragma unroll
            for (int i = 0; i < 32; i++) st.p[i] = 0;
            st.l0 = st.l1 = 0.f;
            st.ready = false;
#pragma unroll 1
            for (int it = 0; it < 4; it++) {
                const int sb = item_block(it, tp);
                const bool trail = (wgi ^ it) & 1;
                const int rsel = trail ? rank : 3 - rank;
                const int nfull = 2 * sb + (trail ? 0 : 1);
                item_head(c, st, it > 0, trail, pv_acc, 2 + it);
                if (rsel & 1) diag_turn<true>(c, st, trail);
                else diag_turn<false>(c, st, trail);
                pv_acc = 0;
#pragma unroll 1
                for (int t = 0; t < nfull; t++) {
                    full_turn(c, st, pv_acc, rsel == 2 && !pv_acc);
                    pv_acc = 1;
                }
                const int rb = 4 * sb + rsel;
                st.odst = g_ctx + ((4 * cg + item_head_index(it)) * 16 + (rb >> 1)) * 2048 + ((rb & 1) * 64 + warp * 16) * 4;
                PROF(4 + it);
            }
            float i0, i1;
            {
                uint32_t vs;
                c.take1(st.ready, vs);
                TR(c, 31);
                c.turn_wait();
                wg_fence();
                issue_pv(st.o, st.p, base + vs * SLOT_BYTES, pv_acc);
                wg_commit();
                if (wgi == 0) c.turn_pass();
                i0 = rcp(quad_sum(st.l0)) * V_UNSCALE;
                i1 = rcp(quad_sum(st.l1)) * V_UNSCALE;
                wg_wait<0>();
                pin<64>(st.o);
                c.release(vs);
            }
            PROF(8);
            TR(c, 32);
            {
                float acc[128];
                uint32_t as = 0, bs0, bs1 = 0;
#pragma unroll 1
                for (int n = 0; n < 8; n++) {
                    const uint32_t pas = as, pbs = bs1;
                    const uint32_t b0 = desc_lo(c.take(bs0), 8192);
                    const uint32_t ab = desc_lo(c.take(as) + wgi * 4096, 16);
                    if (n == 7 && wgi == 1) {
                        wg_wait<0>();
                        c.release(pas);
                        c.release(pbs);
                        bar_sync(5, 256);
                    }
                    wg_fence();
#pragma unroll
                    for (int k = 0; k < 4; k++) wgmma_ss_n256(acc, ab + (k >> 1) * 512 + (k & 1) * 2, b0 + k * 128, (n | k) != 0);
                    wg_commit();
                    TR(c, 80);
                    if (n > 0 && !(n == 7 && wgi == 1)) { wg_wait<1>(); c.release(pas); c.release(pbs); }
                    const uint32_t b1 = desc_lo(c.take(bs1), 8192);
                    wg_fence();
#pragma unroll
                    for (int k = 0; k < 4; k++) wgmma_ss_n256(acc, ab + 1024 + (k >> 1) * 512 + (k & 1) * 2, b1 + k * 128, 1);
                    wg_commit();
                    if (n == 7 && wgi == 0) bar_arrive(5, 256);
                    TR(c, 81);
                    wg_wait<1>();
                    c.release(bs0);
                    if (n == 0) {
                        store_tile(st.odst, lane, st.o, i0, i1);
                        c.signal(6);
                    }
                }
                wg_wait<0>();
                pin<128>(acc);
                c.release(as);
                c.release(bs1);
                PROF(9);
                TR(c, 50);
                const int ks = cg >> 1;
                const int cta0 = (tp + (cg & 1) * 8) * 2 + rank;
                const int t256 = wgi * 128 + warp * 32 + lane;
                const uint32_t par = epoch() & 1;
#pragma unroll
                for (int x = 1; x < 4; x++) {
                    uint4* dst = g_xch + ((cta0 + 32 * ((ks + x) & 3)) * 3 + x - 1) * 1024 + t256;
#pragma unroll
                    for (int j = 0; j < 4; j++) {
                        const float* v = acc + x * 32 + 8 * j;
                        st_relaxed_128(dst + j * 256, (pack2(v[0], v[1]) & ~1u) | par, pack2(v[2], v[3]), pack2(v[4], v[5]), pack2(v[6], v[7]));
                    }
                }
                TR(c, 51);
                float oa[32];
                uint32_t wdesc = 0, slot;
                const uint4* src = g_xch + (cta0 + 32 * ks) * 3 * 1024 + t256;
                uint32_t v[48];
                int spins = 0;
#pragma unroll 1
                for (int x = 0; x < 4; x++) {
                    if (x == 3) {
                        TR(c, 52);
                        while (true) {
                            uint32_t w = par;
                            if (lane < 3) asm volatile("ld.relaxed.gpu.global.u32 %0, [%1];" : "=r"(w) : "l"(src + lane * 1023 + 768) : "memory");
                            if (!__any_sync(~0u, (w ^ par) & 1)) break;
                            if (++spins > (1 << 20)) asm volatile("trap;");
                        }
#pragma unroll
                        for (int j = 0; j < 12; j++) ld_relaxed_128(src + j * 256, v + 4 * j);
                    }
                    wdesc = (x & 1) ? wdesc + 1024 : desc_lo(c.take(slot), 16);
                    const uint32_t ad = desc_lo(c.take(slot) + wgi * 8192, 16);
                    wg_fence();
#pragma unroll
                    for (int k = 0; k < 8; k++) wgmma_ss_n64(oa, ad + (k >> 2) * 1024 + (k & 3) * 2, wdesc + k * 128, x | k);
                    wg_commit();
                }
                const uint32_t stage = c.take(slot) + (wgi * 4 + warp) * 4096;
                __nv_bfloat16* orow = prm.out + (size_t)(tb * 128 + wgi * 64 + warp * 16) * 1024;
                wg_wait<0>();
                pin<32>(oa);
                store_out64(orow + ((cg & 1) - (int)rank) * 128 * 1024 + ks * 128 + rank * 64, stage, lane, oa);
                while (true) {
                    uint32_t bad = 0;
#pragma unroll
                    for (int j = 0; j < 12; j++) bad |= v[4 * j] ^ par;
                    if (!__any_sync(~0u, bad & 1)) break;
                    if (++spins > (1 << 20)) asm volatile("trap;");
#pragma unroll
                    for (int j = 0; j < 12; j++) ld_relaxed_128(src + j * 256, v + 4 * j);
                }
                TR(c, 53);
                const uint32_t eye = (lane >> 3) == (lane & 3) ? ((lane & 4) ? 0x3F800000u : 0x00003F80u) : 0u;
#pragma unroll
                for (int j = 0; j < 12; j++) {
                    v[4 * j] &= ~1u;
                    mma16816(acc + (j & 3) * 8, v + 4 * j, eye, 0u);
                    mma16816(acc + (j & 3) * 8 + 4, v + 4 * j, 0u, eye);
                }
                store_out64(orow + 512 + (cg & 1) * 256 + ks * 64, stage + 2048, lane, acc);
            }
            TR(c, 55);
            PROF(10);
        } else {
            uint4* qa = g_qa + (blockIdx.x - 128) * (16 * 8 * 256) + wgi * 128 + warp * 32 + lane;
            {
                uint32_t a[128];
                float acc[64];
                c.load_tokens<0, 4>(a);
#pragma unroll 1
                for (int i = 0; i < 16; i++) {
                    c.proj_tile(acc, a);
                    const bool next = (i & 3) == 3 && i < 15;
                    if (next) c.load_tokens<0, 3>(a);
#pragma unroll
                    for (int hh = 0; hh < 8; hh++) {
                        const float* x = acc + hh * 8;
                        qa[((i ^ 12) * 8 + hh) * 256] = make_uint4(pack2(x[0], x[1]), pack2(x[2], x[3]), pack2(x[4], x[5]), pack2(x[6], x[7]));
                    }
                    if (next) c.load_tokens<3, 4>(a);
                }
            }
            PROF(1);
            uint32_t s0, s1, s2;
            uint32_t tab0 = c.take(s0) + lane * 16, tab1 = c.take(s1) + lane * 16;
            const uint32_t stage = c.take(s2) + (wgi * 4 + warp) * 2048;
            pin<1>(&tab0);
            pin<1>(&tab1);
            const uint4* pf = qa - lane + (lane >> 2) * 256 + (lane & 3) * 8;
            asm volatile("prefetch.global.L2 [%0];" ::"l"(pf + 2048));
            asm volatile("prefetch.global.L2 [%0];" ::"l"(pf + 4096));
            float pq[32], mx[8], mn[8];
            uint4 nxt[4];
            auto project = [&](int u) {
                const uint32_t tab = ((u & 4) ? tab1 : tab0) + (u & 3) * 8192;
#pragma unroll
                for (int hh = 0; hh < 4; hh++) {
                    const uint4 wf = lds128(tab + hh * 2048);
                    const uint32_t qp[4] = {nxt[hh].x, nxt[hh].y, nxt[hh].z, nxt[hh].w};
#pragma unroll
                    for (int i = 0; i < 8; i++) pq[hh * 8 + i] = 0.f;
                    mma16816(pq + hh * 8, qp, wf.x, wf.y);
                    mma16816(pq + hh * 8 + 4, qp, wf.z, wf.w);
                    nxt[hh] = qa[(min(u + 1, 31) * 4 + hh) * 256];
                }
                feature_range4(pq, mx, mn);
            };
#pragma unroll
            for (int e = 0; e < 4; e++) nxt[e] = qa[e * 256];
            project(0);
#pragma unroll 1
            for (int u = 0; u < 32; u++) {
                if (lane < 16) asm volatile("prefetch.global.L2 [%0];" ::"l"(pf + min(u + 6, 31) * 1024));
                const uint32_t tab = ((u & 4) ? tab1 : tab0) + (u & 3) * 8192;
                uint32_t phi[32];
                feature_map4<false>(pq, mx, mn, phi);
                project(min(u + 1, 31));
#pragma unroll
                for (int hh = 0; hh < 4; hh++) {
                    const uint4 k0 = lds128(tab + hh * 2048 + 512), k1 = lds128(tab + hh * 2048 + 1024), zf = lds128(tab + hh * 2048 + 1536);
                    float n[24];
#pragma unroll
                    for (int e = 0; e < 24; e++) n[e] = 0.f;
                    mma16816(n + 8, phi + hh * 8, zf.x, zf.y);
                    mma16816(n + 20, phi + hh * 8 + 4, zf.z, zf.w);
                    mma16816(n, phi + hh * 8, k0.x, k0.y);
                    mma16816(n + 4, phi + hh * 8, k0.z, k0.w);
                    mma16816(n + 12, phi + hh * 8 + 4, k1.x, k1.y);
                    mma16816(n + 16, phi + hh * 8 + 4, k1.z, k1.w);
                    uint32_t o[4];
#pragma unroll
                    for (int th = 0; th < 2; th++) {
                        const float dp = n[8 + 2 * th], sp = n[9 + 2 * th], dn = n[20 + 2 * th], sn = n[21 + 2 * th];
                        const float w = rcp(fmaf(dp, sn, sp * fmaf(1e-6f, sn, dn)));
                        const float wp = sn * w, wn = sp * w;
                        o[th] = pack2(fmaf(n[2 * th], wp, n[12 + 2 * th] * wn), fmaf(n[2 * th + 1], wp, n[13 + 2 * th] * wn));
                        o[2 + th] = pack2(fmaf(n[4 + 2 * th], wp, n[16 + 2 * th] * wn), fmaf(n[5 + 2 * th], wp, n[17 + 2 * th] * wn));
                    }
                    stsm4(stage + (lane & 15) * 128 + (((2 * hh + (lane >> 4)) ^ (lane & 7)) << 4), o[0], o[1], o[2], o[3]);
                }
                __syncwarp();
                const int tb = ((cl - 64) * 4 + (u >> 3)) * 2 + rank;
                uint4* dst = g_oa + (tb * 4 + ((u >> 1) & 3)) * 2048 + (u & 1) * 1024 + (wgi * 64 + warp * 16) * 8 + lane;
#pragma unroll
                for (int e = 0; e < 4; e++) {
                    uint4 v;
                    asm volatile("ld.shared.v4.b32 {%0, %1, %2, %3}, [%4];"
                                 : "=r"(v.x), "=r"(v.y), "=r"(v.z), "=r"(v.w) : "r"(stage + e * 512 + lane * 16) : "memory");
                    dst[e * 32] = v;
                }
                __syncwarp();
                if ((u & 7) == 7) {
                    c.signal(u >> 3);
                    PROF(2 + (u >> 3));
                }
            }
            if (wgi == 0) c.turn_wait();
            if (blockIdx.x == 131 && tid == 0) *(volatile unsigned*)&g_epoch = epoch();
        }
        PROF(29);
        PROFT(31);
    } else {
        asm volatile("setmaxnreg.dec.sync.aligned.u32 40;");
        if (warp > 0) {
        asm volatile("barrier.cluster.wait.aligned;" ::: "memory");
        if (warp == 1) {
            if (lane == 0) {
                const CUtensorMap* maps[7] = {&prm.ckv, &prm.wuk, &prm.wuv, &prm.xB, &prm.wq, &prm.woB, &prm.woA};
#pragma unroll
                for (int i = 0; i < 7; i++) asm volatile("prefetch.tensormap [%0];" ::"l"(maps[i]) : "memory");
                const int nev = extra ? 4 : 7;
#pragma unroll 1
                for (int ev = 0; ev < nev; ev++) {
                    mbar_wait_idle(base + OFF_SIG + ev * 8, 0);
                    const int f = extra ? F_OA + ((cl - 64) * 4 + ev) * 2 + rank
                                : ev == 0 ? F_AKV + cg
                                : ev < 3 ? F_HEAD + 2 * cg + ev - 1
                                : F_CTX + (4 * cg + item_head_index(ev - 3)) * 8 + item_block(ev - 3, tp);
                    fence_gpu();
                    flag_add(&g_flags[f * FLAG_STRIDE]);
                }
            }
        } else if (warp == 2) {
            if (lane == 0) {
                const unsigned ep = *(volatile unsigned*)&g_epoch + 1;
                asm volatile("st.shared.u32 [%0], %1;" ::"r"(base + OFF_EPOCH), "r"(ep) : "memory");
                const int ng = extra ? 1 : NGATE;
#pragma unroll 1
                for (int i = 0; i < ng; i++) {
                    const int f = extra ? F_TAB : i < 2 ? F_HEAD + 2 * cg + i
                                : i < 10 ? F_CTX + oproj_head(cg >> 1, i - 2) * 8 + tp : F_OA + tp * 2 + (cg & 1);
                    flag_wait(&g_flags[f * FLAG_STRIDE], ep * (extra ? 132 : i < 2 ? 16 : i < 10 ? 2 : 1));
                    fence_proxy_async();
                    mbar_arrive(base + OFF_GATE + 8 * i);
                }
            }
        } else {
            const unsigned ep = *(volatile unsigned*)&g_epoch + 1;
            if (!extra) {
                const int u = tp * 2 + rank, head = 4 * cg + (u >> 2), part = u & 3;
                const uint4 wf = wphi_frags(wphi_load(prm.wphi, head, lane));
                if (part == 0) g_tab[(head * 4 + 0) * 32 + lane] = wf;
                flag_wait(&g_flags[(F_AKV + cg) * FLAG_STRIDE], ep * 16);
                const float4* src = g_kvpart + head * 32 * 136;
                float4 s = make_float4(0.f, 0.f, 0.f, 0.f);
#pragma unroll 6
                for (int i = 0; i < 32; i++) {
                    const float4 v = __ldcg(src + i * 136 + part * 32 + lane);
                    s.x += v.x; s.y += v.y; s.z += v.z; s.w += v.w;
                }
                float2 z = make_float2(0.f, 0.f);
#pragma unroll
                for (int i = 0; i < 4; i++) {
                    const float2 y = __ldcg(reinterpret_cast<const float2*>(src + ((lane >> 2) * 4 + i) * 136 + 128) + part * 4 + (lane & 3));
                    z.x += y.x; z.y += y.y;
                }
#pragma unroll
                for (int d = 4; d < 32; d <<= 1) {
                    z.x += __shfl_xor_sync(~0u, z.x, d);
                    z.y += __shfl_xor_sync(~0u, z.y, d);
                }
                uint32_t* t = reinterpret_cast<uint32_t*>(g_tab + head * 128);
                t[((1 + (part >> 1)) * 32 + lane) * 4 + (part & 1)] = pack2(s.x, s.y);
                t[((1 + (part >> 1)) * 32 + lane) * 4 + 2 + (part & 1)] = pack2(s.z, s.w);
                t[(3 * 32 + lane) * 4 + part] = (lane & 4) ? 0x3F803F80u : pack2(z.x, z.y);
                __syncwarp();
            }
            if (lane == 0) {
                fence_gpu();
                flag_add(&g_flags[F_TAB * FLAG_STRIDE]);
            }
        }
        } else {
            uint32_t lead;
            asm volatile("{ .reg .pred p; elect.sync _|p, 0xffffffff; selp.u32 %0, 1, 0, p; }" : "=r"(lead));
            Producer p{base, rank, lead != 0, {0, 0}};
            const int row0 = (extra ? (cl - 64) * 4 + 3 : tp) * 256 + rank * 128;
            p.token_slot(&prm.xA, 0, row0, false);
            asm volatile("barrier.cluster.wait.aligned;" ::: "memory");
            if (!extra) {
                const int ks = cg >> 1;
#pragma unroll
                for (int s = 0; s < 4; s++) {
                    if (s) p.token_slot(&prm.xA, s, row0, false);
                    p.weight_slot(&prm.wqkv, 512 + 512 * rank + 64 * cg, s, s == 3);
                }
                { uint32_t bar; p.acquire(0, bar); }
                p.tokens(&prm.ckv, row0);
#pragma unroll 1
                for (int j = 0; j < 8; j++) {
                    p.wtile((j & 1) ? &prm.wuv : &prm.wuk, (4 * cg + (j >> 1)) * 128 + 64 * rank);
                    if (rank == 0 && lead)
                        prefetch_box(j >= 6 ? &prm.wq : (j & 1) ? &prm.wuv : &prm.wuk,
                                     (4 * cg + (j >= 6 ? j - 4 : (j >> 1) + 1)) * 128 + 64 * (tp & 1), (tp >> 1) * 128);
                    if (j == 5 && lead)
                        asm volatile("cp.async.bulk.prefetch.tensor.3d.L2.global [%0, {0, %1, %2}];"
                                     ::"l"(&prm.xB), "r"(row0 + (cg & 1) * 64), "r"(cg & 6) : "memory");
                }
                const uint4* vh = nullptr;
                int done = 0, next_pf = PF1;
#pragma unroll 1
                for (int it = 0; it < 4; it++) {
                    const int sb = item_block(it, tp), h = 4 * cg + item_head_index(it);
#pragma unroll 1
                    for (int s = 0; s < 4; s++) {
                        uint32_t bar, dst = p.acquire(SLOT_BYTES, bar);
                        if (lead) {
#pragma unroll
                            for (int w = 0; w < 2; w++) {
                                const int row = 256 * sb + 64 * (((w ^ it) & 1) ? rank : 3 - rank);
                                tma_load3(dst + w * 16384, &prm.xB, row, 2 * s, bar);
                            }
                        }
                        p.weight_slot(&prm.wq, h * 128 + 64 * rank, s);
                        if (s == 0 && it > 0) p.shared_tile(vh);
                    }
                    if (it < 2) p.gate(it);
                    done += 2;
                    if (it == 3 && lead) {
#pragma unroll 1
                        for (int n = 0; n < 4; n++)
                            prefetch_box(&prm.woB, (cg & 1) * 256 + n * 64, oproj_head(ks, tp) * 128 + rank * 64);
                    }
                    const uint4* kh = g_k + h * 16 * 2048;
                    vh = g_v + h * 16 * 2048;
                    p.shared_tile(kh + (2 * sb + 1) * 2048);
#pragma unroll 1
                    for (int t = 2 * sb; t >= 0; t--) {
                        p.shared_tile(vh + (t + 1) * 2048);
                        p.shared_tile(kh + t * 2048);
                        if (++done >= next_pf) {
                            const int hp = 4 * cg + (next_pf == PF1 ? 1 : 0), o = (hp * 16 + tp * 2 + rank) * 2048;
                            if (lead) {
                                if (rank == 0) prefetch_box(&prm.wq, hp * 128 + 64 * (tp & 1), (tp >> 1) * 128);
                                if (PF_KV) {
                                    prefetch_bulk(g_k + o, SLOT_BYTES);
                                    prefetch_bulk(g_v + o, SLOT_BYTES);
                                }
                            }
                            next_pf = next_pf == PF1 ? PF2 : 1000;
                        }
                        if (it == 3 && t == min(2, 2 * sb)) {
                            p.gate(5);
#pragma unroll 1
                            for (int n = 0; n < 4; n++)
                                if (lead) prefetch_bulk(g_ctx + (oproj_head(ks, n) * 16 + tp * 2 + rank) * 2048 + (cg & 1) * 1024, 16384);
                        }
                    }
                }
                p.shared_tile(vh);
                if (lead) prefetch_box(&prm.woA, ks * 128 + rank * 64, (tp & 3) * 128);
#pragma unroll 1
                for (int n = 0; n < 8; n++) {
                    const int h = oproj_head(ks, n);
#pragma unroll
                    for (int kh = 0; kh < 2; kh++) {
                        if (kh) {
                            p.gate(2 + n);
                            p.private_tile(g_ctx + (h * 16 + tp * 2 + rank) * 2048);
                        }
                        uint32_t bar, dst = p.acquire(SLOT_BYTES, bar);
                        if (lead) {
#pragma unroll
                            for (int x = 0; x < 2; x++)
                                tma_load_mc(dst + (rank * 2 + x) * 8192, &prm.woB, (cg & 1) * 256 + ((ks + rank * 2 + x) & 3) * 64,
                                            h * 128 + kh * 64, bar);
                        }
                    }
                }
                p.gate(10);
#pragma unroll 1
                for (int b = 0; b < 2; b++) {
                    uint32_t bar, dst = p.acquire(SLOT_BYTES, bar);
                    if (lead) {
                        tma_load(dst, &prm.woA, ks * 128 + rank * 64, b * 256, bar);
                        tma_load(dst + 16384, &prm.woA, ks * 128 + rank * 64, b * 256 + 128, bar);
                    }
                    p.shared_tile(g_oa + ((tp * 2 + (cg & 1)) * 4 + b * 2) * 2048);
                    p.shared_tile(g_oa + ((tp * 2 + (cg & 1)) * 4 + b * 2 + 1) * 2048);
                }
                { uint32_t bar; p.acquire(0, bar); }
            } else {
#pragma unroll 1
                for (int b = 0; b < 4; b++) {
#pragma unroll 1
                    for (int s = b ? 0 : 1; s < 4; s++) p.token_slot(&prm.xA, s, row0 - b * 256);
#pragma unroll 1
                    for (int i = 0; i < 4; i++) p.wtile(&prm.wqkv, i * 128 + 64 * rank);
                }
                p.gate(0);
                p.private_tile(g_tab);
                p.private_tile(g_tab + 2048);
                { uint32_t bar; p.acquire(0, bar); }
            }
        }
    }
    if (extra) asm volatile("barrier.cluster.arrive.relaxed;\n barrier.cluster.wait;" ::: "memory");
}

typedef CUresult (*EncodeFn)(CUtensorMap*, CUtensorMapDataType, cuuint32_t, void*, const cuuint64_t*, const cuuint64_t*,
                             const cuuint32_t*, const cuuint32_t*, CUtensorMapInterleave, CUtensorMapSwizzle,
                             CUtensorMapL2promotion, CUtensorMapFloatOOBfill);

void encode(EncodeFn fn, CUtensorMap* m, const void* ptr, uint64_t cols, uint64_t rows, uint32_t box_rows) {
    cuuint64_t dims[2] = {cols, rows};
    cuuint64_t strides[1] = {cols * 2};
    cuuint32_t box[2] = {64, box_rows};
    cuuint32_t es[2] = {1, 1};
    fn(m, CU_TENSOR_MAP_DATA_TYPE_BFLOAT16, 2, const_cast<void*>(ptr), dims, strides, box, es, CU_TENSOR_MAP_INTERLEAVE_NONE,
       CU_TENSOR_MAP_SWIZZLE_128B, CU_TENSOR_MAP_L2_PROMOTION_L2_256B, CU_TENSOR_MAP_FLOAT_OOB_FILL_NONE);
}

void encode_rows(EncodeFn fn, CUtensorMap* m, const void* ptr) {
    cuuint64_t dims[3] = {64, 2048, 8};
    cuuint64_t strides[2] = {1024, 128};
    cuuint32_t box[3] = {64, 64, 2};
    cuuint32_t es[3] = {1, 1, 1};
    fn(m, CU_TENSOR_MAP_DATA_TYPE_BFLOAT16, 3, const_cast<void*>(ptr), dims, strides, box, es, CU_TENSOR_MAP_INTERLEAVE_NONE,
       CU_TENSOR_MAP_SWIZZLE_128B, CU_TENSOR_MAP_L2_PROMOTION_L2_256B, CU_TENSOR_MAP_FLOAT_OOB_FILL_NONE);
}

}

extern "C" void kernel_launch(void* const* d_in, const int* in_sizes, int n_in, void* d_out, int out_size) {
    static EncodeFn fn = nullptr;
    if (!fn) {
        void* p = nullptr;
        cudaDriverEntryPointQueryResult st;
        cudaGetDriverEntryPoint("cuTensorMapEncodeTiled", &p, cudaEnableDefault, &st);
        fn = (EncodeFn)p;
        cudaFuncSetAttribute(fused_kernel, cudaFuncAttributeMaxDynamicSharedMemorySize, SMEM_BYTES);
    }
    Params prm;
    encode(fn, &prm.xA, d_in[0], 512, 2048, 128);
    encode(fn, &prm.wqkv, d_in[1], 1536, 512, 128);
    encode(fn, &prm.woA, d_in[3], 512, 512, 128);
    encode_rows(fn, &prm.xB, d_in[4]);
    encode(fn, &prm.ckv, d_in[5], 512, 2048, 128);
    encode(fn, &prm.wq, d_in[6], 4096, 512, 128);
    encode(fn, &prm.wuk, d_in[7], 4096, 512, 128);
    encode(fn, &prm.wuv, d_in[8], 4096, 512, 128);
    encode(fn, &prm.woB, d_in[9], 512, 4096, 64);
    prm.wphi = (const __nv_bfloat16*)d_in[2];
    prm.out = (__nv_bfloat16*)d_out;
    prm.zero = 0;
    fused_kernel<<<132, 384, SMEM_BYTES, cudaStreamPerThread>>>(prm);
}
```
